```python
import torch

def _softmax(x, axis=-1):
    return torch.softmax(x, dim=axis)
def _gelu(x):
    return torch.nn.functional.gelu(x, approximate="tanh")
def _silu(x):
    return torch.nn.functional.silu(x)
def _sigmoid(x):
    return torch.sigmoid(x)
def _layernorm(x, axis=-1, eps=1e-5):
    m = x.mean(dim=axis, keepdim=True)
    v = x.var(dim=axis, keepdim=True, unbiased=False)
    return (x - m) / torch.sqrt(v + eps)
def _scatter_add(tgt, idx, src, axis=0):
    return tgt.clone().index_add_(axis, idx, src)
def _segment_sum(src, seg, n):
    out = torch.zeros((n,) + src.shape[1:], dtype=src.dtype)
    return out.index_add_(0, seg, src)
def _pad(x, pw):
    flat = tuple(v for pair in reversed(pw) for v in pair)
    return torch.nn.functional.pad(x, flat)

kernel_name = 'gated_mix__mha_block__dense_activation_squared_relu__prompt'

def setup_inputs():

    _w = (lambda a: (lambda t: t.to(torch.bfloat16) if t.is_floating_point() else t)(torch.as_tensor(a)))
    def _A_setup():
        B, S, D, H = 1, 2048, 640, 32
        return {
            "x": _w((lambda *s: torch.randn(*s, dtype=torch.bfloat16) * 0.05)(B, S, D)),
            "wqkv": _w((lambda *s: torch.randn(*s, dtype=torch.bfloat16) * 0.8)(D, 3 * D)),
            "wo": _w((lambda *s: torch.randn(*s, dtype=torch.bfloat16) * 0.1)(D, D)),
        }
    _A_in = _A_setup()

    def _B_setup():
        B, S, D, F = 1, 2048, 640, 1728
        return {
            "x": _w((lambda *s: torch.randn(*s, dtype=torch.bfloat16) * 0.05)(B, S, D)),
            "w1": _w((lambda *s: torch.randn(*s, dtype=torch.bfloat16) * 0.1)(D, F)),
            "b1": _w((lambda *s: torch.randn(*s, dtype=torch.bfloat16) * 0.1)(F)),
            "w2": _w((lambda *s: torch.randn(*s, dtype=torch.bfloat16) * 0.1)(F, D)),
            "b2": _w((lambda *s: torch.randn(*s, dtype=torch.bfloat16) * 0.05)(D)),
        }
    _B_in = _B_setup()

    return {
        "A_x": _A_in["x"],
        "A_wqkv": _A_in["wqkv"],
        "A_wo": _A_in["wo"],
        "B_x": _B_in["x"],
        "B_w1": _B_in["w1"],
        "B_b1": _B_in["b1"],
        "B_w2": _B_in["w2"],
        "B_b2": _B_in["b2"],
        "gate_w": _w((lambda *s: torch.randn(*s, dtype=torch.bfloat16) * 0.05)(640) * 16.0),
    }

def reference(A_x, A_wqkv, A_wo, B_x, B_w1, B_b1, B_w2, B_b2, gate_w):
    def _A_ref(x, wqkv, wo):
        B, S, D = x.shape
        H = 32
        Dh = D // H
        qkv = (lambda x, *d: x.permute(*d))((x @ wqkv).reshape(B, S, 3, H, Dh), 2, 0, 3, 1, 4)
        q, k, v = qkv[0], qkv[1], qkv[2]
        scores = torch.einsum("bhqd,bhkd->bhqk", q, k) * (Dh ** -0.5)
        p = _softmax(scores, axis=-1)
        o = torch.einsum("bhqk,bhkd->bhqd", p, v)
        return (lambda x, *d: x.permute(*d))(o, 0, 2, 1, 3).reshape(B, S, D) @ wo

    def _B_ref(x, w1, b1, w2, b2):
        h = torch.einsum("bsd,df->bsf", x, w1) + b1
        zero = torch.zeros_like(h)
        r = torch.where(h > zero, h, zero)
        h = r * r
        out = torch.einsum("bsf,fd->bsd", h, w2) + b2
        return out

    x = A_x
    g = _sigmoid((x * gate_w).sum(-1, keepdims=True))
    a = _A_ref(x, A_wqkv, A_wo)
    b = _B_ref(x, B_w1, B_b1, B_w2, B_b2)
    return g * a + (1 - g) * b
```

```cpp
#include <cuda_runtime.h>
#include <cuda_bf16.h>
#include <cuda.h>
#include <stdint.h>

namespace {

constexpr int S_ = 2048, D_ = 640, NH = 32, F_ = 1728;

__device__ __align__(1024) uint8_t g_Q[NH * 256 * 512];
__device__ __align__(1024) uint8_t g_KV[NH * 256 * 768];
__device__ __align__(1024) uint8_t g_A2[16 * 296 * 2048];
__device__ float g_gate[S_];
__device__ float g_norm[96 * 128];

constexpr uint32_t MUFU_MASK = 0x5151u;

__device__ __forceinline__ uint32_t smem_u32(const void* p) { return (uint32_t)__cvta_generic_to_shared(p); }
__device__ __forceinline__ void wg_fence() { asm volatile("wgmma.fence.sync.aligned;" ::: "memory"); }
__device__ __forceinline__ void wg_commit() { asm volatile("wgmma.commit_group.sync.aligned;" ::: "memory"); }
template <int N> __device__ __forceinline__ void wg_wait() { asm volatile("wgmma.wait_group.sync.aligned %0;" ::"n"(N) : "memory"); }
template <int N> __device__ __forceinline__ void fence_regs(float (&r)[N]) {
#pragma unroll
  for (int i = 0; i < N; i++) asm volatile("" : "+f"(r[i])::"memory");
}
__device__ __forceinline__ float ex2(float x) { float y; asm("ex2.approx.ftz.f32 %0, %1;" : "=f"(y) : "f"(x)); return y; }
__device__ __forceinline__ uint32_t pack_bf16(float lo, float hi) { uint32_t y; asm("cvt.rn.bf16x2.f32 %0, %1, %2;" : "=r"(y) : "f"(hi), "f"(lo)); return y; }
__device__ __forceinline__ uint32_t hfma2_bf16(uint32_t a, uint32_t b, uint32_t c) { uint32_t y; asm("fma.rn.bf16x2 %0, %1, %2, %3;" : "=r"(y) : "r"(a), "r"(b), "r"(c)); return y; }
__device__ __forceinline__ float bf_lo(uint32_t v) { return __uint_as_float(v << 16); }
__device__ __forceinline__ float bf_hi(uint32_t v) { return __uint_as_float(v & 0xffff0000u); }
__device__ __forceinline__ void mbar_init(uint32_t bar, int cnt) { asm volatile("mbarrier.init.shared::cta.b64 [%0], %1;" ::"r"(bar), "r"(cnt)); }
__device__ __forceinline__ void mbar_expect_tx(uint32_t bar, uint32_t bytes) { asm volatile("mbarrier.arrive.expect_tx.shared::cta.b64 _, [%0], %1;" ::"r"(bar), "r"(bytes) : "memory"); }
__device__ __forceinline__ void mbar_arrive(uint32_t bar) { asm volatile("mbarrier.arrive.shared::cta.b64 _, [%0];" ::"r"(bar) : "memory"); }
__device__ __forceinline__ void mbar_arrive_cluster(uint32_t cluster_addr) { asm volatile("mbarrier.arrive.shared::cluster.b64 _, [%0];" ::"r"(cluster_addr) : "memory"); }
__device__ __forceinline__ void mbar_wait(uint32_t bar, uint32_t parity) {
  asm volatile(
      "{\n.reg .pred p;\n.reg .u32 n;\n"
      "mbarrier.try_wait.parity.shared::cta.b64 p, [%0], %1;\n"
      "@p bra DONE;\n"
      "mov.u32 n, 0;\n"
      "LOOP:\n"
      "mbarrier.try_wait.parity.shared::cta.b64 p, [%0], %1;\n"
      "@p bra DONE;\n"
      "add.u32 n, n, 1;\n"
      "setp.lt.u32 p, n, 0x1000000;\n"
      "@p bra LOOP;\n"
      "trap;\n"
      "DONE:\n}\n" ::"r"(bar), "r"(parity) : "memory");
}
__device__ __forceinline__ void bulk_g2s(uint32_t dst, const void* src, uint32_t bytes, uint32_t bar) {
  asm volatile("cp.async.bulk.shared::cluster.global.mbarrier::complete_tx::bytes [%0], [%1], %2, [%3];" ::"r"(dst), "l"(src), "r"(bytes), "r"(bar) : "memory");
}
__device__ __forceinline__ void tma_2d(uint32_t dst, const CUtensorMap* m, int c0, int c1, uint32_t bar) {
  asm volatile("cp.async.bulk.tensor.2d.shared::cluster.global.mbarrier::complete_tx::bytes [%0], [%1, {%3, %4}], [%2];" ::"r"(dst), "l"(m), "r"(bar), "r"(c0), "r"(c1) : "memory");
}
__device__ __forceinline__ void tma_2d_mc(uint32_t dst, const CUtensorMap* m, int c0, int c1, uint32_t bar, uint16_t mask) {
  asm volatile("cp.async.bulk.tensor.2d.shared::cluster.global.mbarrier::complete_tx::bytes.multicast::cluster [%0], [%1, {%3, %4}], [%2], %5;" ::"r"(dst), "l"(m), "r"(bar), "r"(c0), "r"(c1), "h"(mask) : "memory");
}
__device__ __forceinline__ uint32_t mapa(uint32_t addr, uint32_t rank) { uint32_t r; asm("mapa.shared::cluster.u32 %0, %1, %2;" : "=r"(r) : "r"(addr), "r"(rank)); return r; }
__device__ __forceinline__ uint32_t cluster_rank() { uint32_t r; asm("mov.u32 %0, %%cluster_ctarank;" : "=r"(r)); return r; }
__device__ __forceinline__ void cluster_arrive() { asm volatile("barrier.cluster.arrive.release.aligned;" ::: "memory"); }
__device__ __forceinline__ void cluster_wait() { asm volatile("barrier.cluster.wait.acquire.aligned;" ::: "memory"); }
__device__ __forceinline__ void pdl_launch() { asm volatile("griddepcontrol.launch_dependents;" ::: "memory"); }
__device__ __forceinline__ void pdl_wait() { asm volatile("griddepcontrol.wait;" ::: "memory"); }
__device__ __forceinline__ void fence_barrier_init() { asm volatile("fence.mbarrier_init.release.cluster;" ::: "memory"); }
__device__ __forceinline__ void fence_proxy_async() { asm volatile("fence.proxy.async.shared::cta;" ::: "memory"); }
__device__ __forceinline__ void prefetch_tmap(const CUtensorMap* m) { asm volatile("prefetch.tensormap [%0];" ::"l"(m) : "memory"); }
__device__ __forceinline__ uint64_t mk_desc(uint32_t addr, uint32_t lbo, uint32_t sbo, uint32_t mode) {
  return (uint64_t)((addr & 0x3FFFF) >> 4) | ((uint64_t)(lbo >> 4) << 16) | ((uint64_t)(sbo >> 4) << 32) | ((uint64_t)mode << 62);
}

__device__ __forceinline__ void wgmma_ssp_n240_t01(float (&d)[120], uint64_t da, uint64_t db, int sd) {
  asm volatile("{\n.reg .pred p;\nsetp.ne.b32 p, %122, 0;\n"
    "wgmma.mma_async.sync.aligned.m64n240k16.f32.bf16.bf16 {%0, %1, %2, %3, %4, %5, %6, %7, %8, %9, %10, %11, %12, %13, %14, %15, %16, %17, %18, %19, %20, %21, %22, %23, %24, %25, %26, %27, %28, %29, %30, %31, %32, %33, %34, %35, %36, %37, %38, %39, %40, %41, %42, %43, %44, %45, %46, %47, %48, %49, %50, %51, %52, %53, %54, %55, %56, %57, %58, %59, %60, %61, %62, %63, %64, %65, %66, %67, %68, %69, %70, %71, %72, %73, %74, %75, %76, %77, %78, %79, %80, %81, %82, %83, %84, %85, %86, %87, %88, %89, %90, %91, %92, %93, %94, %95, %96, %97, %98, %99, %100, %101, %102, %103, %104, %105, %106, %107, %108, %109, %110, %111, %112, %113, %114, %115, %116, %117, %118, %119}, %120, %121, p, 1, 1, 0, 1;\n}\n"
    : "+f"(d[0]), "+f"(d[1]), "+f"(d[2]), "+f"(d[3]), "+f"(d[4]), "+f"(d[5]), "+f"(d[6]), "+f"(d[7]), "+f"(d[8]), "+f"(d[9]), "+f"(d[10]), "+f"(d[11]), "+f"(d[12]), "+f"(d[13]), "+f"(d[14]), "+f"(d[15]), "+f"(d[16]), "+f"(d[17]), "+f"(d[18]), "+f"(d[19]), "+f"(d[20]), "+f"(d[21]), "+f"(d[22]), "+f"(d[23]), "+f"(d[24]), "+f"(d[25]), "+f"(d[26]), "+f"(d[27]), "+f"(d[28]), "+f"(d[29]), "+f"(d[30]), "+f"(d[31]), "+f"(d[32]), "+f"(d[33]), "+f"(d[34]), "+f"(d[35]), "+f"(d[36]), "+f"(d[37]), "+f"(d[38]), "+f"(d[39]), "+f"(d[40]), "+f"(d[41]), "+f"(d[42]), "+f"(d[43]), "+f"(d[44]), "+f"(d[45]), "+f"(d[46]), "+f"(d[47]), "+f"(d[48]), "+f"(d[49]), "+f"(d[50]), "+f"(d[51]), "+f"(d[52]), "+f"(d[53]), "+f"(d[54]), "+f"(d[55]), "+f"(d[56]), "+f"(d[57]), "+f"(d[58]), "+f"(d[59]), "+f"(d[60]), "+f"(d[61]), "+f"(d[62]), "+f"(d[63]), "+f"(d[64]), "+f"(d[65]), "+f"(d[66]), "+f"(d[67]), "+f"(d[68]), "+f"(d[69]), "+f"(d[70]), "+f"(d[71]), "+f"(d[72]), "+f"(d[73]), "+f"(d[74]), "+f"(d[75]), "+f"(d[76]), "+f"(d[77]), "+f"(d[78]), "+f"(d[79]), "+f"(d[80]), "+f"(d[81]), "+f"(d[82]), "+f"(d[83]), "+f"(d[84]), "+f"(d[85]), "+f"(d[86]), "+f"(d[87]), "+f"(d[88]), "+f"(d[89]), "+f"(d[90]), "+f"(d[91]), "+f"(d[92]), "+f"(d[93]), "+f"(d[94]), "+f"(d[95]), "+f"(d[96]), "+f"(d[97]), "+f"(d[98]), "+f"(d[99]), "+f"(d[100]), "+f"(d[101]), "+f"(d[102]), "+f"(d[103]), "+f"(d[104]), "+f"(d[105]), "+f"(d[106]), "+f"(d[107]), "+f"(d[108]), "+f"(d[109]), "+f"(d[110]), "+f"(d[111]), "+f"(d[112]), "+f"(d[113]), "+f"(d[114]), "+f"(d[115]), "+f"(d[116]), "+f"(d[117]), "+f"(d[118]), "+f"(d[119])
    : "l"(da), "l"(db), "r"(sd));
}
__device__ __forceinline__ void wgmma_ssp_n216_t01(float (&d)[108], uint64_t da, uint64_t db, int sd) {
  asm volatile("{\n.reg .pred p;\nsetp.ne.b32 p, %110, 0;\n"
    "wgmma.mma_async.sync.aligned.m64n216k16.f32.bf16.bf16 {%0, %1, %2, %3, %4, %5, %6, %7, %8, %9, %10, %11, %12, %13, %14, %15, %16, %17, %18, %19, %20, %21, %22, %23, %24, %25, %26, %27, %28, %29, %30, %31, %32, %33, %34, %35, %36, %37, %38, %39, %40, %41, %42, %43, %44, %45, %46, %47, %48, %49, %50, %51, %52, %53, %54, %55, %56, %57, %58, %59, %60, %61, %62, %63, %64, %65, %66, %67, %68, %69, %70, %71, %72, %73, %74, %75, %76, %77, %78, %79, %80, %81, %82, %83, %84, %85, %86, %87, %88, %89, %90, %91, %92, %93, %94, %95, %96, %97, %98, %99, %100, %101, %102, %103, %104, %105, %106, %107}, %108, %109, p, 1, 1, 0, 1;\n}\n"
    : "+f"(d[0]), "+f"(d[1]), "+f"(d[2]), "+f"(d[3]), "+f"(d[4]), "+f"(d[5]), "+f"(d[6]), "+f"(d[7]), "+f"(d[8]), "+f"(d[9]), "+f"(d[10]), "+f"(d[11]), "+f"(d[12]), "+f"(d[13]), "+f"(d[14]), "+f"(d[15]), "+f"(d[16]), "+f"(d[17]), "+f"(d[18]), "+f"(d[19]), "+f"(d[20]), "+f"(d[21]), "+f"(d[22]), "+f"(d[23]), "+f"(d[24]), "+f"(d[25]), "+f"(d[26]), "+f"(d[27]), "+f"(d[28]), "+f"(d[29]), "+f"(d[30]), "+f"(d[31]), "+f"(d[32]), "+f"(d[33]), "+f"(d[34]), "+f"(d[35]), "+f"(d[36]), "+f"(d[37]), "+f"(d[38]), "+f"(d[39]), "+f"(d[40]), "+f"(d[41]), "+f"(d[42]), "+f"(d[43]), "+f"(d[44]), "+f"(d[45]), "+f"(d[46]), "+f"(d[47]), "+f"(d[48]), "+f"(d[49]), "+f"(d[50]), "+f"(d[51]), "+f"(d[52]), "+f"(d[53]), "+f"(d[54]), "+f"(d[55]), "+f"(d[56]), "+f"(d[57]), "+f"(d[58]), "+f"(d[59]), "+f"(d[60]), "+f"(d[61]), "+f"(d[62]), "+f"(d[63]), "+f"(d[64]), "+f"(d[65]), "+f"(d[66]), "+f"(d[67]), "+f"(d[68]), "+f"(d[69]), "+f"(d[70]), "+f"(d[71]), "+f"(d[72]), "+f"(d[73]), "+f"(d[74]), "+f"(d[75]), "+f"(d[76]), "+f"(d[77]), "+f"(d[78]), "+f"(d[79]), "+f"(d[80]), "+f"(d[81]), "+f"(d[82]), "+f"(d[83]), "+f"(d[84]), "+f"(d[85]), "+f"(d[86]), "+f"(d[87]), "+f"(d[88]), "+f"(d[89]), "+f"(d[90]), "+f"(d[91]), "+f"(d[92]), "+f"(d[93]), "+f"(d[94]), "+f"(d[95]), "+f"(d[96]), "+f"(d[97]), "+f"(d[98]), "+f"(d[99]), "+f"(d[100]), "+f"(d[101]), "+f"(d[102]), "+f"(d[103]), "+f"(d[104]), "+f"(d[105]), "+f"(d[106]), "+f"(d[107])
    : "l"(da), "l"(db), "r"(sd));
}
__device__ __forceinline__ void wgmma_ssp_n160_t01(float (&d)[80], uint64_t da, uint64_t db, int sd) {
  asm volatile("{\n.reg .pred p;\nsetp.ne.b32 p, %82, 0;\n"
    "wgmma.mma_async.sync.aligned.m64n160k16.f32.bf16.bf16 {%0, %1, %2, %3, %4, %5, %6, %7, %8, %9, %10, %11, %12, %13, %14, %15, %16, %17, %18, %19, %20, %21, %22, %23, %24, %25, %26, %27, %28, %29, %30, %31, %32, %33, %34, %35, %36, %37, %38, %39, %40, %41, %42, %43, %44, %45, %46, %47, %48, %49, %50, %51, %52, %53, %54, %55, %56, %57, %58, %59, %60, %61, %62, %63, %64, %65, %66, %67, %68, %69, %70, %71, %72, %73, %74, %75, %76, %77, %78, %79}, %80, %81, p, 1, 1, 0, 1;\n}\n"
    : "+f"(d[0]), "+f"(d[1]), "+f"(d[2]), "+f"(d[3]), "+f"(d[4]), "+f"(d[5]), "+f"(d[6]), "+f"(d[7]), "+f"(d[8]), "+f"(d[9]), "+f"(d[10]), "+f"(d[11]), "+f"(d[12]), "+f"(d[13]), "+f"(d[14]), "+f"(d[15]), "+f"(d[16]), "+f"(d[17]), "+f"(d[18]), "+f"(d[19]), "+f"(d[20]), "+f"(d[21]), "+f"(d[22]), "+f"(d[23]), "+f"(d[24]), "+f"(d[25]), "+f"(d[26]), "+f"(d[27]), "+f"(d[28]), "+f"(d[29]), "+f"(d[30]), "+f"(d[31]), "+f"(d[32]), "+f"(d[33]), "+f"(d[34]), "+f"(d[35]), "+f"(d[36]), "+f"(d[37]), "+f"(d[38]), "+f"(d[39]), "+f"(d[40]), "+f"(d[41]), "+f"(d[42]), "+f"(d[43]), "+f"(d[44]), "+f"(d[45]), "+f"(d[46]), "+f"(d[47]), "+f"(d[48]), "+f"(d[49]), "+f"(d[50]), "+f"(d[51]), "+f"(d[52]), "+f"(d[53]), "+f"(d[54]), "+f"(d[55]), "+f"(d[56]), "+f"(d[57]), "+f"(d[58]), "+f"(d[59]), "+f"(d[60]), "+f"(d[61]), "+f"(d[62]), "+f"(d[63]), "+f"(d[64]), "+f"(d[65]), "+f"(d[66]), "+f"(d[67]), "+f"(d[68]), "+f"(d[69]), "+f"(d[70]), "+f"(d[71]), "+f"(d[72]), "+f"(d[73]), "+f"(d[74]), "+f"(d[75]), "+f"(d[76]), "+f"(d[77]), "+f"(d[78]), "+f"(d[79])
    : "l"(da), "l"(db), "r"(sd));
}
__device__ __forceinline__ void wgmma_ss_n64_t00(float (&d)[32], uint64_t da, uint64_t db) {
  asm volatile("{\n.reg .pred p;\nsetp.ne.b32 p, 1, 0;\n"
    "wgmma.mma_async.sync.aligned.m64n64k16.f32.bf16.bf16 {%0, %1, %2, %3, %4, %5, %6, %7, %8, %9, %10, %11, %12, %13, %14, %15, %16, %17, %18, %19, %20, %21, %22, %23, %24, %25, %26, %27, %28, %29, %30, %31}, %32, %33, p, 1, 1, 0, 0;\n}\n"
    : "+f"(d[0]), "+f"(d[1]), "+f"(d[2]), "+f"(d[3]), "+f"(d[4]), "+f"(d[5]), "+f"(d[6]), "+f"(d[7]), "+f"(d[8]), "+f"(d[9]), "+f"(d[10]), "+f"(d[11]), "+f"(d[12]), "+f"(d[13]), "+f"(d[14]), "+f"(d[15]), "+f"(d[16]), "+f"(d[17]), "+f"(d[18]), "+f"(d[19]), "+f"(d[20]), "+f"(d[21]), "+f"(d[22]), "+f"(d[23]), "+f"(d[24]), "+f"(d[25]), "+f"(d[26]), "+f"(d[27]), "+f"(d[28]), "+f"(d[29]), "+f"(d[30]), "+f"(d[31])
    : "l"(da), "l"(db));
}
__device__ __forceinline__ void wgmma_ss0_n64_t00(float (&d)[32], uint64_t da, uint64_t db) {
  asm volatile("{\n.reg .pred p;\nsetp.ne.b32 p, 0, 0;\n"
    "wgmma.mma_async.sync.aligned.m64n64k16.f32.bf16.bf16 {%0, %1, %2, %3, %4, %5, %6, %7, %8, %9, %10, %11, %12, %13, %14, %15, %16, %17, %18, %19, %20, %21, %22, %23, %24, %25, %26, %27, %28, %29, %30, %31}, %32, %33, p, 1, 1, 0, 0;\n}\n"
    : "=f"(d[0]), "=f"(d[1]), "=f"(d[2]), "=f"(d[3]), "=f"(d[4]), "=f"(d[5]), "=f"(d[6]), "=f"(d[7]), "=f"(d[8]), "=f"(d[9]), "=f"(d[10]), "=f"(d[11]), "=f"(d[12]), "=f"(d[13]), "=f"(d[14]), "=f"(d[15]), "=f"(d[16]), "=f"(d[17]), "=f"(d[18]), "=f"(d[19]), "=f"(d[20]), "=f"(d[21]), "=f"(d[22]), "=f"(d[23]), "=f"(d[24]), "=f"(d[25]), "=f"(d[26]), "=f"(d[27]), "=f"(d[28]), "=f"(d[29]), "=f"(d[30]), "=f"(d[31])
    : "l"(da), "l"(db));
}
__device__ __forceinline__ void wgmma_rs_n24_t1(float (&d)[12], uint32_t a0, uint32_t a1, uint32_t a2, uint32_t a3, uint64_t db, int sd) {
  asm volatile("{\n.reg .pred p;\nsetp.ne.b32 p, %17, 0;\n"
    "wgmma.mma_async.sync.aligned.m64n24k16.f32.bf16.bf16 {%0, %1, %2, %3, %4, %5, %6, %7, %8, %9, %10, %11}, {%12, %13, %14, %15}, %16, p, 1, 1, 1;\n}\n"
    : "+f"(d[0]), "+f"(d[1]), "+f"(d[2]), "+f"(d[3]), "+f"(d[4]), "+f"(d[5]), "+f"(d[6]), "+f"(d[7]), "+f"(d[8]), "+f"(d[9]), "+f"(d[10]), "+f"(d[11])
    : "r"(a0), "r"(a1), "r"(a2), "r"(a3), "l"(db), "r"(sd));
}

constexpr int K1_NST = 4;
constexpr int K1_A_BYTES = 10 * 16384;
constexpr int K1_SMEM = K1_A_BYTES + K1_NST * 16384 + 1024 + 1024;

template <int BN, typename MMA>
__device__ __forceinline__ void k1_mainloop(float (&acc)[BN / 2], MMA mma, uint32_t sA, uint32_t sB, uint32_t barA, uint32_t barF,
                                            uint32_t barE, uint32_t barE_peer, int it0, bool waitA, int wgi, bool elect) {
  const uint64_t dA0 = mk_desc(sA + wgi * 8192, 16, 1024, 1);
  const uint64_t dB0 = mk_desc(sB, 4096, 1024, 1);
  fence_regs(acc);
#pragma unroll 1
  for (int s = 0; s < 20; s++) {
    const int it = it0 + s, st = it & (K1_NST - 1);
    if (waitA && !(s & 1)) mbar_wait(barA + 8 * (s >> 1), 0);
    mbar_wait(barF + 8 * st, (it / K1_NST) & 1);
    const uint64_t da = dA0 + (uint32_t)((s >> 1) * 1024 + (s & 1) * 4);
    const uint64_t db = dB0 + (uint32_t)(st * 1024);
    wg_fence();
    mma(acc, da, db, s);
    mma(acc, da + 2, db + 128, 1);
    wg_commit();
    if (s > 0) {
      wg_wait<1>();
      if (elect) { const int ps = (it - 1) & (K1_NST - 1); mbar_arrive_cluster(barE + 8 * ps); mbar_arrive_cluster(barE_peer + 8 * ps); }
    }
  }
  wg_wait<0>();
  fence_regs(acc);
  if (elect) { const int ps = (it0 + 19) & (K1_NST - 1); mbar_arrive_cluster(barE + 8 * ps); mbar_arrive_cluster(barE_peer + 8 * ps); }
}

__global__ void __cluster_dims__(2, 1, 1) __launch_bounds__(384, 1)
k1_proj(const __grid_constant__ CUtensorMap tmX, const __grid_constant__ CUtensorMap tmWqkv, const __grid_constant__ CUtensorMap tmW1,
        const __nv_bfloat16* __restrict__ b1, const __nv_bfloat16* __restrict__ gate_w) {
  extern __shared__ uint8_t smem_raw[];
  const uint32_t sb = (smem_u32(smem_raw) + 1023u) & ~1023u;
  const uint32_t sA = sb, sB = sb + K1_A_BYTES, bars = sB + K1_NST * 16384;
  const uint32_t barA = bars, barF = bars + 80, barE = barF + 8 * K1_NST;
  const int tid = threadIdx.x, lane = tid & 31;
  const int warp = __shfl_sync(0xffffffffu, tid >> 5, 0);
  const int rb = blockIdx.x & 15, cg = blockIdx.x >> 4;
  const uint32_t rank = cluster_rank();
  if (tid == 0) {
    prefetch_tmap(&tmX); prefetch_tmap(&tmWqkv); prefetch_tmap(&tmW1);
    for (int i = 0; i < 10; i++) mbar_init(barA + 8 * i, 1);
    for (int i = 0; i < K1_NST; i++) { mbar_init(barF + 8 * i, 1); mbar_init(barE + 8 * i, 16); }
    fence_barrier_init();
  }
  pdl_launch();
  cluster_arrive();
  cluster_wait();

  if (warp < 4) {
    if (warp == 0) {
      if (lane == 0) {
        mbar_expect_tx(barA, 16384);
        tma_2d(sA, &tmX, 0, rb * 128, barA);
#pragma unroll 1
        for (int it = 0; it < 40; it++) {
          const int st = it & (K1_NST - 1);
          if (it >= K1_NST) mbar_wait(barE + 8 * st, ((it / K1_NST) - 1) & 1);
          mbar_expect_tx(barF + 8 * st, 16384);
          const bool t0 = it < 20;
          const CUtensorMap* m = t0 ? &tmWqkv : &tmW1;
          const int col = (t0 ? cg * 240 : cg * 216) + (int)rank * 128;
          const int k = (t0 ? it : it - 20) * 32;
          const uint32_t dst = sB + st * 16384 + rank * 8192;
          tma_2d_mc(dst, m, col, k, barF + 8 * st, (uint16_t)3);
          tma_2d_mc(dst + 4096, m, col + 64, k, barF + 8 * st, (uint16_t)3);
          if (it < 9) {
            const int kb = it + 1;
            mbar_expect_tx(barA + 8 * kb, 16384);
            tma_2d(sA + kb * 16384, &tmX, kb * 64, rb * 128, barA + 8 * kb);
          }
        }
      }
    } else if (warp == 1) {
      const int r = cg * 16 + (lane >> 1), half = lane & 1;
      float acc = 0.f;
#pragma unroll 1
      for (int kb = half * 5; kb < half * 5 + 5; kb++) {
        mbar_wait(barA + 8 * kb, 0);
#pragma unroll
        for (int c = 0; c < 8; c++) {
          uint4 xv;
          asm volatile("ld.shared.v4.u32 {%0,%1,%2,%3}, [%4];" : "=r"(xv.x), "=r"(xv.y), "=r"(xv.z), "=r"(xv.w)
                       : "r"(sA + kb * 16384 + r * 128 + ((c ^ (r & 7)) << 4)));
          const uint4 wv = __ldg(reinterpret_cast<const uint4*>(gate_w + kb * 64 + c * 8));
          acc = fmaf(bf_lo(xv.x), bf_lo(wv.x), acc); acc = fmaf(bf_hi(xv.x), bf_hi(wv.x), acc);
          acc = fmaf(bf_lo(xv.y), bf_lo(wv.y), acc); acc = fmaf(bf_hi(xv.y), bf_hi(wv.y), acc);
          acc = fmaf(bf_lo(xv.z), bf_lo(wv.z), acc); acc = fmaf(bf_hi(xv.z), bf_hi(wv.z), acc);
          acc = fmaf(bf_lo(xv.w), bf_lo(wv.w), acc); acc = fmaf(bf_hi(xv.w), bf_hi(wv.w), acc);
        }
      }
      acc += __shfl_xor_sync(0xffffffffu, acc, 1);
      if (!half) g_gate[rb * 128 + r] = 1.f / (1.f + __expf(-acc));
    }
  } else {
    const int wgi = (warp >> 2) - 1, wq = warp & 3, g = lane >> 2, t4 = lane & 3;
    const uint32_t barE_self = mapa(barE, rank), barE_peer = mapa(barE, rank ^ 1);
    const bool elect = lane == 0;
    const int rloc = wgi * 64 + wq * 16 + g;
    {
      float acc[120];
      k1_mainloop<240>(acc, [](float (&d)[120], uint64_t a, uint64_t b, int sd) { wgmma_ssp_n240_t01(d, a, b, sd); },
                       sA, sB, barA, barF, barE_self, barE_peer, 0, true, wgi, elect);
      const int grp = rb * 16 + wgi * 8 + wq * 2;
      const bool poly0 = !((MUFU_MASK >> (grp & 15)) & 1), poly1 = !((MUFU_MASK >> ((grp + 1) & 15)) & 1);
      float ssA0 = 0.f, ssA1 = 0.f, ssB0 = 0.f, ssB1 = 0.f;
#pragma unroll
      for (int j = 0; j < 30; j++) {
        const int lhA = (4 * j) / 10;
        const int thr = (lhA + 1) * 10 - 4 * j;
        const bool hiH = t4 >= thr;
        const int lh = lhA + (hiH ? 1 : 0);
        const int p = 4 * j + t4 - lh * 10;
        const int slot = cg * 12 + lh, which = slot >> 5, head = slot & 31;
        const float sc = which == 0 ? 0.32259642f : 1.0f;
        const float v0 = acc[4 * j] * sc, v1 = acc[4 * j + 1] * sc, v2 = acc[4 * j + 2] * sc, v3 = acc[4 * j + 3] * sc;
        uint8_t* base = which == 0 ? g_Q + (size_t)head * 131072 + grp * 512 : g_KV + (size_t)head * 196608 + grp * 768 + (which == 2 ? 384 : 0);
        const int gstride = which == 0 ? 512 : 768;
        uint8_t* ptr = base + (p >> 2) * 128 + g * 16 + (p & 3) * 4;
        *reinterpret_cast<uint32_t*>(ptr) = pack_bf16(v0, v1);
        *reinterpret_cast<uint32_t*>(ptr + gstride) = pack_bf16(v2, v3);
        if (p == 9) {
          uint2 c0, c1;
          if (which == 0) { c0 = make_uint2(0x42FB47C0u, 0x0000BDCCu); c1 = c0; }
          else if (which == 1) { c0 = poly0 ? make_uint2(0x3F803F80u, 0x00003F80u) : make_uint2(0u, 0u);
                                 c1 = poly1 ? make_uint2(0x3F803F80u, 0x00003F80u) : make_uint2(0u, 0u); }
          else { c0 = make_uint2(0x00003F80u, 0u); c1 = c0; }
          *reinterpret_cast<uint2*>(ptr + 4) = c0;
          *reinterpret_cast<uint2*>(ptr + 4 + gstride) = c1;
        }
        if (p == 8 && which == 0) {
          *reinterpret_cast<uint4*>(ptr + 128) = make_uint4(0, 0, 0, 0);
          *reinterpret_cast<uint4*>(ptr + 128 + 512) = make_uint4(0, 0, 0, 0);
        }
        const float q0 = fmaf(v0, v0, v1 * v1), q1 = fmaf(v2, v2, v3 * v3);
        if (hiH) { ssB0 += q0; ssB1 += q1; } else { ssA0 += q0; ssA1 += q1; }
        if (thr <= 4) {
          float a0 = ssA0, a1 = ssA1;
          a0 += __shfl_xor_sync(0xffffffffu, a0, 1); a1 += __shfl_xor_sync(0xffffffffu, a1, 1);
          a0 += __shfl_xor_sync(0xffffffffu, a0, 2); a1 += __shfl_xor_sync(0xffffffffu, a1, 2);
          float m = fmaxf(a0, a1);
          m = fmaxf(m, __shfl_xor_sync(0xffffffffu, m, 4));
          m = fmaxf(m, __shfl_xor_sync(0xffffffffu, m, 8));
          m = fmaxf(m, __shfl_xor_sync(0xffffffffu, m, 16));
          if (lane == 0) g_norm[(cg * 12 + lhA) * 128 + rb * 8 + wgi * 4 + wq] = m;
          ssA0 = ssB0; ssA1 = ssB1; ssB0 = 0.f; ssB1 = 0.f;
        }
      }
    }
    {
      float acc[108];
      k1_mainloop<216>(acc, [](float (&d)[108], uint64_t a, uint64_t b, int sd) { wgmma_ssp_n216_t01(d, a, b, sd); },
                       sA, sB, barA, barF, barE_self, barE_peer, 20, false, wgi, elect);
      uint8_t* base = g_A2 + ((size_t)(rb * 296 + cg * 27) * 16 + (rloc >> 3)) * 128 + g * 16 + t4 * 4;
      const uint32_t* bp = reinterpret_cast<const uint32_t*>(b1 + cg * 216 + t4 * 2);
#pragma unroll
      for (int j = 0; j < 27; j++) {
        const uint32_t bv = __ldg(bp + j * 4);
        const float c0 = bf_lo(bv), c1 = bf_hi(bv);
        float h0 = fmaxf(acc[4 * j] + c0, 0.f), h1 = fmaxf(acc[4 * j + 1] + c1, 0.f);
        float h2 = fmaxf(acc[4 * j + 2] + c0, 0.f), h3 = fmaxf(acc[4 * j + 3] + c1, 0.f);
        *reinterpret_cast<uint32_t*>(base + j * 2048) = pack_bf16(h0 * h0, h1 * h1);
        *reinterpret_cast<uint32_t*>(base + j * 2048 + 128) = pack_bf16(h2 * h2, h3 * h3);
      }
    }
  }
  __syncwarp();
  cluster_arrive();
  cluster_wait();
}

constexpr int KV_HEAD_BYTES = 256 * 768, Q_BYTES = 8 * 4096;
constexpr int AT_NCHUNK = 16, AT_CHUNK_BYTES = KV_HEAD_BYTES / AT_NCHUNK;
constexpr int AT_SMEM = KV_HEAD_BYTES + Q_BYTES + 1024 + 1024;

template <int T0, int T1, int TOFF>
__device__ __forceinline__ void exp_tiles(const float (&s)[32], uint32_t (&p)[16], uint32_t cmask, uint32_t cone) {
#pragma unroll
  for (int t = T0; t < T1; t++) {
#pragma unroll
    for (int h = 0; h < 2; h++) {
      const float x0 = s[4 * t + 2 * h], x1 = s[4 * t + 2 * h + 1];
      uint32_t r;
      if ((MUFU_MASK >> ((t + TOFF) & 15)) & 1) {
        r = pack_bf16(ex2(x0), ex2(x1));
      } else {
        const uint32_t u = __byte_perm(__float_as_uint(x0), __float_as_uint(x1), 0x5410);
        uint32_t g;
        asm("lop3.b32 %0, %1, %2, %3, 0xEA;" : "=r"(g) : "r"(u), "r"(cmask), "r"(cone));
        r = hfma2_bf16(g, g, 0x40034003u) + u - g;
      }
      p[2 * t + h] = r;
      asm volatile("" : "+r"(p[2 * t + h])::"memory");
    }
  }
}
template <int TOFF>
__device__ __forceinline__ void exp_pv(const float (&s)[32], uint32_t (&p)[16], float (&o)[12], uint64_t dv, int sd, uint32_t cmask, uint32_t cone) {
  exp_tiles<0, 4, TOFF>(s, p, cmask, cone);
  wg_fence();
  wgmma_rs_n24_t1(o, p[0], p[1], p[2], p[3], dv, sd);
  wgmma_rs_n24_t1(o, p[4], p[5], p[6], p[7], dv + 96, 1);
  exp_tiles<4, 8, TOFF>(s, p, cmask, cone);
  wg_fence();
  wgmma_rs_n24_t1(o, p[8], p[9], p[10], p[11], dv + 192, 1);
  wgmma_rs_n24_t1(o, p[12], p[13], p[14], p[15], dv + 288, 1);
}
__device__ __forceinline__ void qk64(float (&s)[32], uint64_t dq, uint64_t dk) {
  wgmma_ss0_n64_t00(s, dq, dk);
  wgmma_ss_n64_t00(s, dq + 16, dk + 16);
}
__device__ __forceinline__ void attn_store(const float (&o)[12], int row0, int head, int lane) {
  const int t4 = lane & 3;
  const float l0 = __shfl_sync(0xffffffffu, o[8], (lane & ~3) | 2), l1 = __shfl_sync(0xffffffffu, o[10], (lane & ~3) | 2);
  const float r0 = __fdividef(g_gate[row0], l0), r1 = __fdividef(g_gate[row0 + 8], l1);
  uint8_t* base = g_A2 + ((size_t)((row0 >> 7) * 296 + 216) * 16 + ((row0 & 127) >> 3)) * 128 + (row0 & 7) * 16;
#pragma unroll
  for (int tt = 0; tt < 3; tt++) {
    const int d = tt * 8 + 2 * t4;
    if (d < 20) {
      const int col = head * 20 + d;
      uint8_t* ptr = base + (col >> 3) * 2048 + (col & 7) * 2;
      *reinterpret_cast<uint32_t*>(ptr) = pack_bf16(o[4 * tt] * r0, o[4 * tt + 1] * r0);
      *reinterpret_cast<uint32_t*>(ptr + 128) = pack_bf16(o[4 * tt + 2] * r1, o[4 * tt + 3] * r1);
    }
  }
}

__device__ __forceinline__ void attn_slow(uint32_t sb, uint32_t bb, int wg, int rowbase, int head, int lane) {
  const uint64_t dk0 = mk_desc(sb, 128, 768, 0), dv0 = mk_desc(sb + 384, 768, 128, 0);
  const uint64_t dq0 = mk_desc(sb + KV_HEAD_BYTES + wg * 8192, 128, 512, 0);
#pragma unroll 1
  for (int mt = 0; mt < 2; mt++) {
    float o[12], s[32];
    uint32_t p[16];
#pragma unroll
    for (int i = 0; i < 12; i++) o[i] = 0.f;
    float m0 = -INFINITY, m1 = -INFINITY;
#pragma unroll 1
    for (int b = 0; b < 32; b++) {
      if (mt == 0 && !(b & 1)) mbar_wait(bb + 8 * (b >> 1), 0);
      wg_fence();
      qk64(s, dq0 + (uint32_t)(mt * 256), dk0 + (uint32_t)(b * 384));
      wg_commit();
      wg_wait<0>();
      fence_regs(s);
      float n0 = m0, n1 = m1;
#pragma unroll
      for (int t = 0; t < 8; t++) { n0 = fmaxf(n0, fmaxf(s[4 * t], s[4 * t + 1])); n1 = fmaxf(n1, fmaxf(s[4 * t + 2], s[4 * t + 3])); }
      n0 = fmaxf(n0, __shfl_xor_sync(0xffffffffu, n0, 1)); n0 = fmaxf(n0, __shfl_xor_sync(0xffffffffu, n0, 2));
      n1 = fmaxf(n1, __shfl_xor_sync(0xffffffffu, n1, 1)); n1 = fmaxf(n1, __shfl_xor_sync(0xffffffffu, n1, 2));
      const float a0 = ex2(m0 - n0), a1 = ex2(m1 - n1);
      m0 = n0; m1 = n1;
#pragma unroll
      for (int t = 0; t < 3; t++) { o[4 * t] *= a0; o[4 * t + 1] *= a0; o[4 * t + 2] *= a1; o[4 * t + 3] *= a1; }
#pragma unroll
      for (int t = 0; t < 8; t++) {
        p[2 * t] = pack_bf16(ex2(s[4 * t] - m0), ex2(s[4 * t + 1] - m0));
        p[2 * t + 1] = pack_bf16(ex2(s[4 * t + 2] - m1), ex2(s[4 * t + 3] - m1));
      }
      fence_regs(o);
      wg_fence();
#pragma unroll
      for (int k = 0; k < 4; k++) wgmma_rs_n24_t1(o, p[4 * k], p[4 * k + 1], p[4 * k + 2], p[4 * k + 3], dv0 + (uint32_t)(b * 384 + k * 96), 1);
      wg_commit();
      wg_wait<0>();
      fence_regs(o);
    }
    attn_store(o, rowbase + mt * 64, head, lane);
  }
}

__global__ void __launch_bounds__(512, 1) k2_attn(int opaque_zero) {
  extern __shared__ uint8_t smem_raw[];
  const uint32_t sb = (smem_u32(smem_raw) + 1023u) & ~1023u;
  const uint32_t bb = sb + KV_HEAD_BYTES + Q_BYTES;
  const int tid = threadIdx.x, lane = tid & 31;
  const int warp = __shfl_sync(0xffffffffu, tid >> 5, 0), wg = warp >> 2;
  const int head = blockIdx.x >> 2, qb = blockIdx.x & 3;
  if (tid == 0) {
    for (int i = 0; i <= AT_NCHUNK; i++) mbar_init(bb + 8 * i, 1);
    fence_barrier_init();
    fence_proxy_async();
  }
  pdl_launch();
  pdl_wait();
  if (tid == 0) {
    mbar_expect_tx(bb + 8 * AT_NCHUNK, Q_BYTES);
    bulk_g2s(sb + KV_HEAD_BYTES, g_Q + (size_t)blockIdx.x * Q_BYTES, Q_BYTES, bb + 8 * AT_NCHUNK);
    for (int i = 0; i < AT_NCHUNK; i++) {
      mbar_expect_tx(bb + 8 * i, AT_CHUNK_BYTES);
      bulk_g2s(sb + i * AT_CHUNK_BYTES, g_KV + (size_t)head * KV_HEAD_BYTES + i * AT_CHUNK_BYTES, AT_CHUNK_BYTES, bb + 8 * i);
    }
  }
  bool fast;
  {
    float nq = g_norm[head * 128 + qb * 32 + lane];
    const float4 k4 = *reinterpret_cast<const float4*>(&g_norm[(32 + head) * 128 + lane * 4]);
    const float4 v4 = *reinterpret_cast<const float4*>(&g_norm[(64 + head) * 128 + lane * 4]);
    float nk = fmaxf(fmaxf(k4.x, k4.y), fmaxf(k4.z, k4.w)), nv = fmaxf(fmaxf(v4.x, v4.y), fmaxf(v4.z, v4.w));
    bool bad = !(nq == nq) || !(k4.x + k4.y + k4.z + k4.w == k4.x + k4.y + k4.z + k4.w) || !(v4.x + v4.y + v4.z + v4.w == v4.x + v4.y + v4.z + v4.w);
#pragma unroll
    for (int o = 16; o; o >>= 1) {
      nq = fmaxf(nq, __shfl_xor_sync(0xffffffffu, nq, o));
      nk = fmaxf(nk, __shfl_xor_sync(0xffffffffu, nk, o));
      nv = fmaxf(nv, __shfl_xor_sync(0xffffffffu, nv, o));
    }
    bad = __any_sync(0xffffffffu, bad);
    fast = !bad && (nq * nk <= 2304.0f) && (nq <= 1e30f) && (nk <= 1e30f) && (nv <= 1e30f) && (nv >= 1e-18f);
  }
  const int rowbase = qb * 512 + wg * 128 + (warp & 3) * 16 + (lane >> 2);
  __syncthreads();
  mbar_wait(bb + 8 * AT_NCHUNK, 0);
  if (!fast) {
    *reinterpret_cast<uint2*>(smem_raw + (sb - smem_u32(smem_raw)) + KV_HEAD_BYTES + (tid >> 3) * 512 + 256 + (tid & 7) * 16 + 8) = make_uint2(0u, 0u);
    fence_proxy_async();
    __syncthreads();
    attn_slow(sb, bb, wg, rowbase, head, lane);
    return;
  }
  uint32_t cmask = 0x007F007Fu + opaque_zero, cone = 0x3F803F80u + opaque_zero;
  const uint64_t dk0 = mk_desc(sb, 128, 768, 0), dv0 = mk_desc(sb + 384, 768, 128, 0);
  const uint64_t dq0 = mk_desc(sb + KV_HEAD_BYTES + wg * 8192, 128, 512, 0);
  float o[12], s0[32], s1[32];
  uint32_t p0[16], p1[16];
#pragma unroll
  for (int i = 0; i < 12; i++) o[i] = 0.f;
  fence_regs(o);
  mbar_wait(bb, 0);
  wg_fence();
  qk64(s0, dq0, dk0);
  wg_commit();
  wg_wait<0>();
  fence_regs(s0);
#pragma unroll 1
  for (int it = 0; it < 32; it++) {
    const int c = it & 15, mt = it >> 4;
    const uint64_t dq = dq0 + (uint32_t)(mt * 256);
    const uint32_t off = c * 768;
    wg_fence();
    qk64(s1, dq, dk0 + (off + 384));
    wg_commit();
    exp_pv<0>(s0, p0, o, dv0 + off, c, cmask, cone);
    wg_commit();
    wg_wait<1>();
    fence_regs(s1);
    const int cn = (c + 1) & 15;
    const uint64_t dqn = dq0 + (uint32_t)((((it + 1) >> 4) & 1) * 256);
    if (it < 15) mbar_wait(bb + 8 * cn, 0);
    wg_fence();
    qk64(s0, dqn, dk0 + (uint32_t)(cn * 768));
    wg_commit();
    exp_pv<8>(s1, p1, o, dv0 + (off + 384), 1, cmask, cone);
    wg_commit();
    wg_wait<0>();
    fence_regs(s0);
    fence_regs(o);
    if (c == 15) attn_store(o, rowbase + mt * 64, head, lane);
  }
}

constexpr int K3_NST = 8, K3_STAGE = 8192 + 10240;
constexpr int K3_RED = 128 * 80 * 4;
constexpr int K3_SMEM = K3_NST * K3_STAGE + K3_RED + 1024 + 1024;

__global__ void __cluster_dims__(2, 1, 1) __launch_bounds__(288, 1)
k3_out(const __grid_constant__ CUtensorMap tmW2, const __grid_constant__ CUtensorMap tmWo, const __nv_bfloat16* __restrict__ b2,
       __nv_bfloat16* __restrict__ out) {
  extern __shared__ uint8_t smem_raw[];
  const uint32_t sb = (smem_u32(smem_raw) + 1023u) & ~1023u;
  const uint32_t sRed = sb + K3_NST * K3_STAGE, barF = sRed + K3_RED, barE = barF + 8 * K3_NST;
  const int tid = threadIdx.x, lane = tid & 31;
  const int warp = __shfl_sync(0xffffffffu, tid >> 5, 0);
  const uint32_t rank = cluster_rank();
  const int tile = blockIdx.x >> 1, rb = tile >> 2, ct = tile & 3;
  if (tid == 0) {
    prefetch_tmap(&tmW2); prefetch_tmap(&tmWo);
    for (int i = 0; i < K3_NST; i++) { mbar_init(barF + 8 * i, 1); mbar_init(barE + 8 * i, 8); }
    fence_barrier_init();
  }
  __syncthreads();
  if (warp == 8) {
    if (lane == 0) {
      const int s0 = rank * 37;
      const uint8_t* asrc = g_A2 + (size_t)rb * 296 * 2048;
      for (int i = 0; i < K3_NST; i++) {
        const int s = s0 + i;
        mbar_expect_tx(barF + 8 * i, K3_STAGE);
        for (int b = 0; b < 5; b++) tma_2d(sb + i * K3_STAGE + 8192 + b * 2048, &tmW2, ct * 160 + b * 32, s * 32, barF + 8 * i);
      }
      pdl_wait();
      for (int i = 0; i < K3_NST; i++) bulk_g2s(sb + i * K3_STAGE, asrc + (size_t)(s0 + i) * 8192, 8192, barF + 8 * i);
#pragma unroll 1
      for (int i = K3_NST; i < 37; i++) {
        const int st = i & (K3_NST - 1), s = s0 + i;
        mbar_wait(barE + 8 * st, ((i / K3_NST) - 1) & 1);
        mbar_expect_tx(barF + 8 * st, K3_STAGE);
        bulk_g2s(sb + st * K3_STAGE, asrc + (size_t)s * 8192, 8192, barF + 8 * st);
        const CUtensorMap* m = s < 54 ? &tmW2 : &tmWo;
        const int k = (s < 54 ? s : s - 54) * 32;
        for (int b = 0; b < 5; b++) tma_2d(sb + st * K3_STAGE + 8192 + b * 2048, m, ct * 160 + b * 32, k, barF + 8 * st);
      }
    }
    __syncwarp();
    cluster_arrive(); cluster_wait();
    cluster_arrive(); cluster_wait();
  } else {
    const int wgi = warp >> 2, wq = warp & 3, g = lane >> 2, t4 = lane & 3;
    const int rloc = wgi * 64 + wq * 16 + g, row = rb * 128 + rloc;
    pdl_wait();
    const float w0 = 1.f - g_gate[row], w1 = 1.f - g_gate[row + 8];
    float acc[80];
    const uint64_t dA0 = mk_desc(sb + wgi * 1024, 2048, 128, 0), dB0 = mk_desc(sb + 8192, 2048, 512, 2);
    const int nsw = rank ? 17 : 37;
    fence_regs(acc);
#pragma unroll 1
    for (int i = 0; i < 37; i++) {
      const int st = i & (K3_NST - 1);
      mbar_wait(barF + 8 * st, (i / K3_NST) & 1);
      const uint32_t off = st * (K3_STAGE >> 4);
      wg_fence();
      wgmma_ssp_n160_t01(acc, dA0 + off, dB0 + off, i);
      wgmma_ssp_n160_t01(acc, dA0 + off + 256, dB0 + off + 64, 1);
      wg_commit();
      if (i + 1 == nsw) {
        wg_wait<0>();
        fence_regs(acc);
#pragma unroll
        for (int j = 0; j < 20; j++) { acc[4 * j] *= w0; acc[4 * j + 1] *= w0; acc[4 * j + 2] *= w1; acc[4 * j + 3] *= w1; }
        fence_regs(acc);
      } else {
        wg_wait<1>();
      }
      if (i > 0 && lane == 0) mbar_arrive(barE + 8 * ((i - 1) & (K3_NST - 1)));
    }
    wg_wait<0>();
    fence_regs(acc);
    cluster_arrive(); cluster_wait();
    const uint32_t peerRed = mapa(sRed, rank ^ 1) + tid * 8;
#pragma unroll
    for (int j = 0; j < 10; j++) {
      const float a0 = rank ? acc[4 * j] : acc[40 + 4 * j], a1 = rank ? acc[4 * j + 1] : acc[40 + 4 * j + 1];
      const float a2 = rank ? acc[4 * j + 2] : acc[40 + 4 * j + 2], a3 = rank ? acc[4 * j + 3] : acc[40 + 4 * j + 3];
      asm volatile("st.shared::cluster.v2.f32 [%0], {%1, %2};" ::"r"(peerRed + (2 * j) * 2048), "f"(a0), "f"(a1) : "memory");
      asm volatile("st.shared::cluster.v2.f32 [%0], {%1, %2};" ::"r"(peerRed + (2 * j + 1) * 2048), "f"(a2), "f"(a3) : "memory");
    }
    cluster_arrive(); cluster_wait();
    const int col0 = ct * 160 + rank * 80 + t4 * 2;
#pragma unroll
    for (int j = 0; j < 10; j++) {
      float p0, p1, p2, p3;
      asm volatile("ld.shared.v2.f32 {%0, %1}, [%2];" : "=f"(p0), "=f"(p1) : "r"(sRed + tid * 8 + (2 * j) * 2048));
      asm volatile("ld.shared.v2.f32 {%0, %1}, [%2];" : "=f"(p2), "=f"(p3) : "r"(sRed + tid * 8 + (2 * j + 1) * 2048));
      const float a0 = rank ? acc[40 + 4 * j] : acc[4 * j], a1 = rank ? acc[40 + 4 * j + 1] : acc[4 * j + 1];
      const float a2 = rank ? acc[40 + 4 * j + 2] : acc[4 * j + 2], a3 = rank ? acc[40 + 4 * j + 3] : acc[4 * j + 3];
      const uint32_t bv = __ldg(reinterpret_cast<const uint32_t*>(b2 + col0 + j * 8));
      const float c0 = bf_lo(bv), c1 = bf_hi(bv);
      *reinterpret_cast<uint32_t*>(out + (size_t)row * D_ + col0 + j * 8) = pack_bf16(fmaf(w0, c0, a0 + p0), fmaf(w0, c1, a1 + p1));
      *reinterpret_cast<uint32_t*>(out + (size_t)(row + 8) * D_ + col0 + j * 8) = pack_bf16(fmaf(w1, c0, a2 + p2), fmaf(w1, c1, a3 + p3));
    }
  }
}

typedef CUresult (*EncodeFn)(CUtensorMap*, CUtensorMapDataType, cuuint32_t, void*, const cuuint64_t*, const cuuint64_t*, const cuuint32_t*,
                             const cuuint32_t*, CUtensorMapInterleave, CUtensorMapSwizzle, CUtensorMapL2promotion, CUtensorMapFloatOOBfill);

void make_map(EncodeFn fn, CUtensorMap* m, const void* ptr, uint64_t inner, uint64_t outer, uint32_t box_inner, uint32_t box_outer, CUtensorMapSwizzle sw) {
  cuuint64_t dims[2] = {inner, outer};
  cuuint64_t strides[1] = {inner * 2};
  cuuint32_t box[2] = {box_inner, box_outer};
  cuuint32_t es[2] = {1, 1};
  fn(m, CU_TENSOR_MAP_DATA_TYPE_BFLOAT16, 2, const_cast<void*>(ptr), dims, strides, box, es, CU_TENSOR_MAP_INTERLEAVE_NONE, sw,
     CU_TENSOR_MAP_L2_PROMOTION_L2_256B, CU_TENSOR_MAP_FLOAT_OOB_FILL_NONE);
}

}

extern "C" void kernel_launch(void* const* d_in, const int* in_sizes, int n_in, void* d_out, int out_size) {
  (void)in_sizes; (void)n_in; (void)out_size;
  const __nv_bfloat16* x = (const __nv_bfloat16*)d_in[0];
  const __nv_bfloat16* wqkv = (const __nv_bfloat16*)d_in[1];
  const __nv_bfloat16* wo = (const __nv_bfloat16*)d_in[2];
  const __nv_bfloat16* w1 = (const __nv_bfloat16*)d_in[4];
  const __nv_bfloat16* b1 = (const __nv_bfloat16*)d_in[5];
  const __nv_bfloat16* w2 = (const __nv_bfloat16*)d_in[6];
  const __nv_bfloat16* b2 = (const __nv_bfloat16*)d_in[7];
  const __nv_bfloat16* gw = (const __nv_bfloat16*)d_in[8];

  static EncodeFn enc = nullptr;
  if (!enc) {
    void* p = nullptr;
    cudaDriverEntryPointQueryResult qr;
    cudaGetDriverEntryPoint("cuTensorMapEncodeTiled", &p, cudaEnableDefault, &qr);
    enc = (EncodeFn)p;
    cudaFuncSetAttribute(k1_proj, cudaFuncAttributeMaxDynamicSharedMemorySize, K1_SMEM);
    cudaFuncSetAttribute(k2_attn, cudaFuncAttributeMaxDynamicSharedMemorySize, AT_SMEM);
    cudaFuncSetAttribute(k3_out, cudaFuncAttributeMaxDynamicSharedMemorySize, K3_SMEM);
  }
  CUtensorMap tmX, tmWqkv, tmW1, tmW2, tmWo;
  make_map(enc, &tmX, x, D_, S_, 64, 128, CU_TENSOR_MAP_SWIZZLE_128B);
  make_map(enc, &tmWqkv, wqkv, 3 * D_, D_, 64, 32, CU_TENSOR_MAP_SWIZZLE_128B);
  make_map(enc, &tmW1, w1, F_, D_, 64, 32, CU_TENSOR_MAP_SWIZZLE_128B);
  make_map(enc, &tmW2, w2, D_, F_, 32, 32, CU_TENSOR_MAP_SWIZZLE_64B);
  make_map(enc, &tmWo, wo, D_, D_, 32, 32, CU_TENSOR_MAP_SWIZZLE_64B);

  cudaStream_t st = cudaStreamPerThread;
  k1_proj<<<128, 384, K1_SMEM, st>>>(tmX, tmWqkv, tmW1, b1, gw);

  cudaLaunchAttribute at[1];
  at[0].id = cudaLaunchAttributeProgrammaticStreamSerialization;
  at[0].val.programmaticStreamSerializationAllowed = 1;
  {
    cudaLaunchConfig_t cfg = {};
    cfg.gridDim = dim3(128); cfg.blockDim = dim3(512); cfg.dynamicSmemBytes = AT_SMEM; cfg.stream = st;
    cfg.attrs = at; cfg.numAttrs = 1;
    cudaLaunchKernelEx(&cfg, k2_attn, 0);
  }
  {
    cudaLaunchConfig_t cfg = {};
    cfg.gridDim = dim3(128); cfg.blockDim = dim3(288); cfg.dynamicSmemBytes = K3_SMEM; cfg.stream = st;
    cfg.attrs = at; cfg.numAttrs = 1;
    cudaLaunchKernelEx(&cfg, k3_out, tmW2, tmWo, b2, (__nv_bfloat16*)d_out);
  }
}
```

```cpp
#include <cuda_runtime.h>
#include <cuda_bf16.h>
#include <cuda.h>
#include <stdint.h>

namespace {

constexpr int S_ = 2048, D_ = 640, NH = 32, F_ = 1728;

constexpr uint32_t KV_OFF = NH * 256 * 512;
__device__ __align__(1024) uint8_t g_QKV[NH * 256 * 512 + NH * 256 * 768];
__device__ __align__(1024) uint8_t g_A2[16 * 296 * 2048];
__device__ float g_gate[S_];
__device__ float g_norm[96 * 64];

constexpr uint32_t MUFU_MASK = 0x5151u;

#define STAMP(i) do { } while (0)

__device__ __forceinline__ uint32_t smem_u32(const void* p) { return (uint32_t)__cvta_generic_to_shared(p); }
__device__ __forceinline__ void wg_fence() { asm volatile("wgmma.fence.sync.aligned;" ::: "memory"); }
__device__ __forceinline__ void wg_commit() { asm volatile("wgmma.commit_group.sync.aligned;" ::: "memory"); }
template <int N> __device__ __forceinline__ void wg_wait() { asm volatile("wgmma.wait_group.sync.aligned %0;" ::"n"(N) : "memory"); }
template <int N> __device__ __forceinline__ void fence_regs(float (&r)[N]) {
#pragma unroll
  for (int i = 0; i < N; i++) asm volatile("" : "+f"(r[i])::"memory");
}
__device__ __forceinline__ float ex2(float x) { float y; asm("ex2.approx.ftz.f32 %0, %1;" : "=f"(y) : "f"(x)); return y; }
__device__ __forceinline__ uint32_t pack_bf16(float lo, float hi) { uint32_t y; asm("cvt.rn.bf16x2.f32 %0, %1, %2;" : "=r"(y) : "f"(hi), "f"(lo)); return y; }
__device__ __forceinline__ uint32_t hfma2_bf16(uint32_t a, uint32_t b, uint32_t c) { uint32_t y; asm("fma.rn.bf16x2 %0, %1, %2, %3;" : "=r"(y) : "r"(a), "r"(b), "r"(c)); return y; }
__device__ __forceinline__ float bf_lo(uint32_t v) { return __uint_as_float(v << 16); }
__device__ __forceinline__ float bf_hi(uint32_t v) { return __uint_as_float(v & 0xffff0000u); }
__device__ __forceinline__ void mbar_init(uint32_t bar, int cnt) { asm volatile("mbarrier.init.shared::cta.b64 [%0], %1;" ::"r"(bar), "r"(cnt)); }
__device__ __forceinline__ void mbar_expect_tx(uint32_t bar, uint32_t bytes) { asm volatile("mbarrier.arrive.expect_tx.shared::cta.b64 _, [%0], %1;" ::"r"(bar), "r"(bytes) : "memory"); }
__device__ __forceinline__ void mbar_arrive(uint32_t bar) { asm volatile("mbarrier.arrive.shared::cta.b64 _, [%0];" ::"r"(bar) : "memory"); }
__device__ __forceinline__ void mbar_arrive_cluster(uint32_t cluster_addr) { asm volatile("mbarrier.arrive.shared::cluster.b64 _, [%0];" ::"r"(cluster_addr) : "memory"); }
__device__ __forceinline__ void mbar_wait(uint32_t bar, uint32_t parity) {
  asm volatile(
      "{\n.reg .pred p;\n.reg .u32 n;\n"
      "mbarrier.try_wait.parity.shared::cta.b64 p, [%0], %1;\n"
      "@p bra DONE;\n"
      "mov.u32 n, 0;\n"
      "LOOP:\n"
      "mbarrier.try_wait.parity.shared::cta.b64 p, [%0], %1;\n"
      "@p bra DONE;\n"
      "add.u32 n, n, 1;\n"
      "setp.lt.u32 p, n, 0x1000000;\n"
      "@p bra LOOP;\n"
      "trap;\n"
      "DONE:\n}\n" ::"r"(bar), "r"(parity) : "memory");
}
__device__ __forceinline__ void bulk_g2s(uint32_t dst, const void* src, uint32_t bytes, uint32_t bar) {
  asm volatile("cp.async.bulk.shared::cluster.global.mbarrier::complete_tx::bytes [%0], [%1], %2, [%3];" ::"r"(dst), "l"(src), "r"(bytes), "r"(bar) : "memory");
}
__device__ __forceinline__ void tma_2d(uint32_t dst, const CUtensorMap* m, int c0, int c1, uint32_t bar) {
  asm volatile("cp.async.bulk.tensor.2d.shared::cluster.global.mbarrier::complete_tx::bytes [%0], [%1, {%3, %4}], [%2];" ::"r"(dst), "l"(m), "r"(bar), "r"(c0), "r"(c1) : "memory");
}
__device__ __forceinline__ void tma_2d_mc(uint32_t dst, const CUtensorMap* m, int c0, int c1, uint32_t bar, uint16_t mask) {
  asm volatile("cp.async.bulk.tensor.2d.shared::cluster.global.mbarrier::complete_tx::bytes.multicast::cluster [%0], [%1, {%3, %4}], [%2], %5;" ::"r"(dst), "l"(m), "r"(bar), "r"(c0), "r"(c1), "h"(mask) : "memory");
}
__device__ __forceinline__ uint32_t mapa(uint32_t addr, uint32_t rank) { uint32_t r; asm("mapa.shared::cluster.u32 %0, %1, %2;" : "=r"(r) : "r"(addr), "r"(rank)); return r; }
__device__ __forceinline__ uint32_t cluster_rank() { uint32_t r; asm("mov.u32 %0, %%cluster_ctarank;" : "=r"(r)); return r; }
__device__ __forceinline__ void cluster_arrive() { asm volatile("barrier.cluster.arrive.release.aligned;" ::: "memory"); }
__device__ __forceinline__ void cluster_arrive_relaxed() { asm volatile("barrier.cluster.arrive.relaxed.aligned;" ::: "memory"); }
__device__ __forceinline__ void cluster_wait() { asm volatile("barrier.cluster.wait.acquire.aligned;" ::: "memory"); }
__device__ __forceinline__ void bar_sync(int id, int n) { asm volatile("bar.sync %0, %1;" ::"r"(id), "r"(n) : "memory"); }
__device__ __forceinline__ void bar_arrive(int id, int n) { asm volatile("bar.arrive %0, %1;" ::"r"(id), "r"(n) : "memory"); }
__device__ __forceinline__ void pdl_launch() { asm volatile("griddepcontrol.launch_dependents;" ::: "memory"); }
__device__ __forceinline__ void pdl_wait() { asm volatile("griddepcontrol.wait;" ::: "memory"); }
__device__ __forceinline__ void fence_barrier_init() { asm volatile("fence.mbarrier_init.release.cluster;" ::: "memory"); }
__device__ __forceinline__ void fence_proxy_async() { asm volatile("fence.proxy.async.shared::cta;" ::: "memory"); }
__device__ __forceinline__ void prefetch_tmap(const CUtensorMap* m) { asm volatile("prefetch.tensormap [%0];" ::"l"(m) : "memory"); }
__device__ __forceinline__ uint64_t mk_desc(uint32_t addr, uint32_t lbo, uint32_t sbo, uint32_t mode) {
  return (uint64_t)((addr & 0x3FFFF) >> 4) | ((uint64_t)(lbo >> 4) << 16) | ((uint64_t)(sbo >> 4) << 32) | ((uint64_t)mode << 62);
}

__device__ __forceinline__ void wgmma_ssp_n120_t01(float (&d)[60], uint64_t da, uint64_t db, int sd) {
  asm volatile("{\n.reg .pred p;\nsetp.ne.b32 p, %62, 0;\n"
    "wgmma.mma_async.sync.aligned.m64n120k16.f32.bf16.bf16 {%0, %1, %2, %3, %4, %5, %6, %7, %8, %9, %10, %11, %12, %13, %14, %15, %16, %17, %18, %19, %20, %21, %22, %23, %24, %25, %26, %27, %28, %29, %30, %31, %32, %33, %34, %35, %36, %37, %38, %39, %40, %41, %42, %43, %44, %45, %46, %47, %48, %49, %50, %51, %52, %53, %54, %55, %56, %57, %58, %59}, %60, %61, p, 1, 1, 0, 1;\n}\n"
    : "+f"(d[0]), "+f"(d[1]), "+f"(d[2]), "+f"(d[3]), "+f"(d[4]), "+f"(d[5]), "+f"(d[6]), "+f"(d[7]), "+f"(d[8]), "+f"(d[9]), "+f"(d[10]), "+f"(d[11]), "+f"(d[12]), "+f"(d[13]), "+f"(d[14]), "+f"(d[15]), "+f"(d[16]), "+f"(d[17]), "+f"(d[18]), "+f"(d[19]), "+f"(d[20]), "+f"(d[21]), "+f"(d[22]), "+f"(d[23]), "+f"(d[24]), "+f"(d[25]), "+f"(d[26]), "+f"(d[27]), "+f"(d[28]), "+f"(d[29]), "+f"(d[30]), "+f"(d[31]), "+f"(d[32]), "+f"(d[33]), "+f"(d[34]), "+f"(d[35]), "+f"(d[36]), "+f"(d[37]), "+f"(d[38]), "+f"(d[39]), "+f"(d[40]), "+f"(d[41]), "+f"(d[42]), "+f"(d[43]), "+f"(d[44]), "+f"(d[45]), "+f"(d[46]), "+f"(d[47]), "+f"(d[48]), "+f"(d[49]), "+f"(d[50]), "+f"(d[51]), "+f"(d[52]), "+f"(d[53]), "+f"(d[54]), "+f"(d[55]), "+f"(d[56]), "+f"(d[57]), "+f"(d[58]), "+f"(d[59])
    : "l"(da), "l"(db), "r"(sd));
}
__device__ __forceinline__ void wgmma_ssp_n112_t01(float (&d)[56], uint64_t da, uint64_t db, int sd) {
  asm volatile("{\n.reg .pred p;\nsetp.ne.b32 p, %58, 0;\n"
    "wgmma.mma_async.sync.aligned.m64n112k16.f32.bf16.bf16 {%0, %1, %2, %3, %4, %5, %6, %7, %8, %9, %10, %11, %12, %13, %14, %15, %16, %17, %18, %19, %20, %21, %22, %23, %24, %25, %26, %27, %28, %29, %30, %31, %32, %33, %34, %35, %36, %37, %38, %39, %40, %41, %42, %43, %44, %45, %46, %47, %48, %49, %50, %51, %52, %53, %54, %55}, %56, %57, p, 1, 1, 0, 1;\n}\n"
    : "+f"(d[0]), "+f"(d[1]), "+f"(d[2]), "+f"(d[3]), "+f"(d[4]), "+f"(d[5]), "+f"(d[6]), "+f"(d[7]), "+f"(d[8]), "+f"(d[9]), "+f"(d[10]), "+f"(d[11]), "+f"(d[12]), "+f"(d[13]), "+f"(d[14]), "+f"(d[15]), "+f"(d[16]), "+f"(d[17]), "+f"(d[18]), "+f"(d[19]), "+f"(d[20]), "+f"(d[21]), "+f"(d[22]), "+f"(d[23]), "+f"(d[24]), "+f"(d[25]), "+f"(d[26]), "+f"(d[27]), "+f"(d[28]), "+f"(d[29]), "+f"(d[30]), "+f"(d[31]), "+f"(d[32]), "+f"(d[33]), "+f"(d[34]), "+f"(d[35]), "+f"(d[36]), "+f"(d[37]), "+f"(d[38]), "+f"(d[39]), "+f"(d[40]), "+f"(d[41]), "+f"(d[42]), "+f"(d[43]), "+f"(d[44]), "+f"(d[45]), "+f"(d[46]), "+f"(d[47]), "+f"(d[48]), "+f"(d[49]), "+f"(d[50]), "+f"(d[51]), "+f"(d[52]), "+f"(d[53]), "+f"(d[54]), "+f"(d[55])
    : "l"(da), "l"(db), "r"(sd));
}
__device__ __forceinline__ void wgmma_ssp_n160_t01(float (&d)[80], uint64_t da, uint64_t db, int sd) {
  asm volatile("{\n.reg .pred p;\nsetp.ne.b32 p, %82, 0;\n"
    "wgmma.mma_async.sync.aligned.m64n160k16.f32.bf16.bf16 {%0, %1, %2, %3, %4, %5, %6, %7, %8, %9, %10, %11, %12, %13, %14, %15, %16, %17, %18, %19, %20, %21, %22, %23, %24, %25, %26, %27, %28, %29, %30, %31, %32, %33, %34, %35, %36, %37, %38, %39, %40, %41, %42, %43, %44, %45, %46, %47, %48, %49, %50, %51, %52, %53, %54, %55, %56, %57, %58, %59, %60, %61, %62, %63, %64, %65, %66, %67, %68, %69, %70, %71, %72, %73, %74, %75, %76, %77, %78, %79}, %80, %81, p, 1, 1, 0, 1;\n}\n"
    : "+f"(d[0]), "+f"(d[1]), "+f"(d[2]), "+f"(d[3]), "+f"(d[4]), "+f"(d[5]), "+f"(d[6]), "+f"(d[7]), "+f"(d[8]), "+f"(d[9]), "+f"(d[10]), "+f"(d[11]), "+f"(d[12]), "+f"(d[13]), "+f"(d[14]), "+f"(d[15]), "+f"(d[16]), "+f"(d[17]), "+f"(d[18]), "+f"(d[19]), "+f"(d[20]), "+f"(d[21]), "+f"(d[22]), "+f"(d[23]), "+f"(d[24]), "+f"(d[25]), "+f"(d[26]), "+f"(d[27]), "+f"(d[28]), "+f"(d[29]), "+f"(d[30]), "+f"(d[31]), "+f"(d[32]), "+f"(d[33]), "+f"(d[34]), "+f"(d[35]), "+f"(d[36]), "+f"(d[37]), "+f"(d[38]), "+f"(d[39]), "+f"(d[40]), "+f"(d[41]), "+f"(d[42]), "+f"(d[43]), "+f"(d[44]), "+f"(d[45]), "+f"(d[46]), "+f"(d[47]), "+f"(d[48]), "+f"(d[49]), "+f"(d[50]), "+f"(d[51]), "+f"(d[52]), "+f"(d[53]), "+f"(d[54]), "+f"(d[55]), "+f"(d[56]), "+f"(d[57]), "+f"(d[58]), "+f"(d[59]), "+f"(d[60]), "+f"(d[61]), "+f"(d[62]), "+f"(d[63]), "+f"(d[64]), "+f"(d[65]), "+f"(d[66]), "+f"(d[67]), "+f"(d[68]), "+f"(d[69]), "+f"(d[70]), "+f"(d[71]), "+f"(d[72]), "+f"(d[73]), "+f"(d[74]), "+f"(d[75]), "+f"(d[76]), "+f"(d[77]), "+f"(d[78]), "+f"(d[79])
    : "l"(da), "l"(db), "r"(sd));
}
__device__ __forceinline__ void wgmma_ss_n64_t00(float (&d)[32], uint64_t da, uint64_t db) {
  asm volatile("{\n.reg .pred p;\nsetp.ne.b32 p, 1, 0;\n"
    "wgmma.mma_async.sync.aligned.m64n64k16.f32.bf16.bf16 {%0, %1, %2, %3, %4, %5, %6, %7, %8, %9, %10, %11, %12, %13, %14, %15, %16, %17, %18, %19, %20, %21, %22, %23, %24, %25, %26, %27, %28, %29, %30, %31}, %32, %33, p, 1, 1, 0, 0;\n}\n"
    : "+f"(d[0]), "+f"(d[1]), "+f"(d[2]), "+f"(d[3]), "+f"(d[4]), "+f"(d[5]), "+f"(d[6]), "+f"(d[7]), "+f"(d[8]), "+f"(d[9]), "+f"(d[10]), "+f"(d[11]), "+f"(d[12]), "+f"(d[13]), "+f"(d[14]), "+f"(d[15]), "+f"(d[16]), "+f"(d[17]), "+f"(d[18]), "+f"(d[19]), "+f"(d[20]), "+f"(d[21]), "+f"(d[22]), "+f"(d[23]), "+f"(d[24]), "+f"(d[25]), "+f"(d[26]), "+f"(d[27]), "+f"(d[28]), "+f"(d[29]), "+f"(d[30]), "+f"(d[31])
    : "l"(da), "l"(db));
}
__device__ __forceinline__ void wgmma_ss0_n64_t00(float (&d)[32], uint64_t da, uint64_t db) {
  asm volatile("{\n.reg .pred p;\nsetp.ne.b32 p, 0, 0;\n"
    "wgmma.mma_async.sync.aligned.m64n64k16.f32.bf16.bf16 {%0, %1, %2, %3, %4, %5, %6, %7, %8, %9, %10, %11, %12, %13, %14, %15, %16, %17, %18, %19, %20, %21, %22, %23, %24, %25, %26, %27, %28, %29, %30, %31}, %32, %33, p, 1, 1, 0, 0;\n}\n"
    : "=f"(d[0]), "=f"(d[1]), "=f"(d[2]), "=f"(d[3]), "=f"(d[4]), "=f"(d[5]), "=f"(d[6]), "=f"(d[7]), "=f"(d[8]), "=f"(d[9]), "=f"(d[10]), "=f"(d[11]), "=f"(d[12]), "=f"(d[13]), "=f"(d[14]), "=f"(d[15]), "=f"(d[16]), "=f"(d[17]), "=f"(d[18]), "=f"(d[19]), "=f"(d[20]), "=f"(d[21]), "=f"(d[22]), "=f"(d[23]), "=f"(d[24]), "=f"(d[25]), "=f"(d[26]), "=f"(d[27]), "=f"(d[28]), "=f"(d[29]), "=f"(d[30]), "=f"(d[31])
    : "l"(da), "l"(db));
}
__device__ __forceinline__ void wgmma_rs_n24_t1(float (&d)[12], uint32_t a0, uint32_t a1, uint32_t a2, uint32_t a3, uint64_t db, int sd) {
  asm volatile("{\n.reg .pred p;\nsetp.ne.b32 p, %17, 0;\n"
    "wgmma.mma_async.sync.aligned.m64n24k16.f32.bf16.bf16 {%0, %1, %2, %3, %4, %5, %6, %7, %8, %9, %10, %11}, {%12, %13, %14, %15}, %16, p, 1, 1, 1;\n}\n"
    : "+f"(d[0]), "+f"(d[1]), "+f"(d[2]), "+f"(d[3]), "+f"(d[4]), "+f"(d[5]), "+f"(d[6]), "+f"(d[7]), "+f"(d[8]), "+f"(d[9]), "+f"(d[10]), "+f"(d[11])
    : "r"(a0), "r"(a1), "r"(a2), "r"(a3), "l"(db), "r"(sd));
}

constexpr int K1_NST = 4;
constexpr int K1_A_BYTES = 10 * 16384;
constexpr int K1_SMEM = K1_A_BYTES + K1_NST * 16384 + 1024 + 1024;

template <int BN, typename MMA>
__device__ __forceinline__ void k1_mainloop(float (&acc0)[BN / 2], float (&acc1)[BN / 2], MMA mma, uint32_t sA, uint32_t sB, uint32_t barA,
                                            uint32_t barF, uint32_t barE, uint32_t barE_peer, int it0, bool waitA, bool elect, int turn_wait, int turn_give) {
  const uint64_t dA0 = mk_desc(sA, 16, 1024, 1);
  const uint64_t dB0 = mk_desc(sB, 8192, 1024, 1);
  fence_regs(acc0); fence_regs(acc1);
  if (turn_wait) bar_sync(turn_wait, 256);
#pragma unroll 1
  for (int s = 0; s < 10; s++) {
    const int it = it0 + s, st = it & (K1_NST - 1);
    if (waitA) mbar_wait(barA + 8 * s, 0);
    mbar_wait(barF + 8 * st, (it / K1_NST) & 1);
    const uint64_t da = dA0 + (uint32_t)(s * 1024);
    const uint64_t db = dB0 + (uint32_t)(st * 1024);
    wg_fence();
#pragma unroll
    for (int k = 0; k < 4; k++) {
      mma(acc0, da + 2 * k, db + 128 * k, k == 0 ? s : 1);
      mma(acc1, da + 512 + 2 * k, db + 128 * k, k == 0 ? s : 1);
    }
    wg_commit();
    if (s > 0) {
      wg_wait<1>();
      if (elect) { const int ps = (it - 1) & (K1_NST - 1); mbar_arrive_cluster(barE + 8 * ps); mbar_arrive_cluster(barE_peer + 8 * ps); }
    }
  }
  if (turn_give) bar_arrive(turn_give, 256);
  wg_wait<0>();
  fence_regs(acc0); fence_regs(acc1);
  if (elect) { const int ps = (it0 + 9) & (K1_NST - 1); mbar_arrive_cluster(barE + 8 * ps); mbar_arrive_cluster(barE_peer + 8 * ps); }
}

__device__ __forceinline__ void st32(uint8_t* p, uint32_t v) { *reinterpret_cast<uint32_t*>(p) = v; }

__device__ __forceinline__ void k1_qkv_epi(const float (&acc)[60], float (&nrm)[6], int slot0, int grp, int g, int t4) {
  const uint32_t tq = grp * 512 + g * 16, tkv = KV_OFF + grp * 768 + g * 16;
  const bool lo2 = t4 < 2;
  const uint32_t e0 = t4 * 4, e2 = lo2 ? 8 + t4 * 4 : 128 + (t4 - 2) * 4;
  const bool poly0 = !((MUFU_MASK >> (grp & 15)) & 1), poly1 = !((MUFU_MASK >> ((grp + 1) & 15)) & 1);
#pragma unroll
  for (int hp = 0; hp < 3; hp++) {
    uint8_t* ptr[2]; uint32_t gs[2]; float sc[2];
#pragma unroll
    for (int e = 0; e < 2; e++) {
      const int slot = slot0 + 2 * hp + e, which = slot >> 5, head = slot & 31;
      gs[e] = which == 0 ? 512u : 768u;
      sc[e] = which == 0 ? 0.32259642f : 1.0f;
      ptr[e] = g_QKV + (which == 0 ? head * 131072u + tq : head * 196608u + (which == 2 ? 384u : 0u) + tkv);
      if (t4 == 0) {
        uint2 c0, c1;
        if (which == 0) { c0 = make_uint2(0x42FB47C0u, 0x0000BDCCu); c1 = c0; }
        else if (which == 1) { c0 = poly0 ? make_uint2(0x3F803F80u, 0x00003F80u) : make_uint2(0u, 0u);
                               c1 = poly1 ? make_uint2(0x3F803F80u, 0x00003F80u) : make_uint2(0u, 0u); }
        else { c0 = make_uint2(0x00003F80u, 0u); c1 = c0; }
        *reinterpret_cast<uint2*>(ptr[e] + 264) = c0;
        *reinterpret_cast<uint2*>(ptr[e] + 264 + gs[e]) = c1;
      } else if (which == 0 && t4 < 3) {
        *reinterpret_cast<uint4*>(ptr[e] + 384 + (t4 - 1) * 512) = make_uint4(0, 0, 0, 0);
      }
    }
    const float scm = lo2 ? sc[0] : sc[1];
    uint8_t* pm = lo2 ? ptr[0] + 256 + e0 : ptr[1] + (e0 - 8);
    const uint32_t gm = lo2 ? gs[0] : gs[1];
    float q[5][2];
#pragma unroll
    for (int jj = 0; jj < 5; jj++) {
      const int j = hp * 5 + jj;
      const float f = jj < 2 ? sc[0] : (jj == 2 ? scm : sc[1]);
      const float v0 = acc[4 * j] * f, v1 = acc[4 * j + 1] * f, v2 = acc[4 * j + 2] * f, v3 = acc[4 * j + 3] * f;
      uint8_t* p = jj < 2 ? ptr[0] + jj * 128 + e0 : (jj == 2 ? pm : ptr[1] + (jj - 3) * 128 + e2);
      const uint32_t gg = jj < 2 ? gs[0] : (jj == 2 ? gm : gs[1]);
      st32(p, pack_bf16(v0, v1));
      st32(p + gg, pack_bf16(v2, v3));
      q[jj][0] = fmaf(v0, v0, v1 * v1);
      q[jj][1] = fmaf(v2, v2, v3 * v3);
    }
#pragma unroll
    for (int r = 0; r < 2; r++) {
      float a = q[0][r] + q[1][r] + (lo2 ? q[2][r] : 0.f), b = q[3][r] + q[4][r] + (lo2 ? 0.f : q[2][r]);
      a += __shfl_xor_sync(0xffffffffu, a, 1); b += __shfl_xor_sync(0xffffffffu, b, 1);
      a += __shfl_xor_sync(0xffffffffu, a, 2); b += __shfl_xor_sync(0xffffffffu, b, 2);
      nrm[2 * hp] = __uint_as_float(max(__float_as_uint(nrm[2 * hp]), __float_as_uint(a)));
      nrm[2 * hp + 1] = __uint_as_float(max(__float_as_uint(nrm[2 * hp + 1]), __float_as_uint(b)));
    }
  }
}

__global__ void __cluster_dims__(2, 1, 1) __launch_bounds__(384, 1)
k1_proj(const __grid_constant__ CUtensorMap tmX, const __grid_constant__ CUtensorMap tmWqkv, const __grid_constant__ CUtensorMap tmW1,
        const __nv_bfloat16* __restrict__ b1, const __nv_bfloat16* __restrict__ gate_w) {
  extern __shared__ uint8_t smem_raw[];
  const uint32_t sb = (smem_u32(smem_raw) + 1023u) & ~1023u;
  const uint32_t sA = sb, sB = sb + K1_A_BYTES, bars = sB + K1_NST * 16384;
  const uint32_t barA = bars, barF = bars + 80, barE = barF + 8 * K1_NST;
  const int tid = threadIdx.x, lane = tid & 31;
  const int warp = __shfl_sync(0xffffffffu, tid >> 5, 0);
  const int rb = blockIdx.x & 15, cg = blockIdx.x >> 4;
  const uint32_t rank = cluster_rank();
  if (tid == 0) {
    STAMP(0);
    prefetch_tmap(&tmX); prefetch_tmap(&tmWqkv); prefetch_tmap(&tmW1);
    for (int i = 0; i < 10; i++) mbar_init(barA + 8 * i, 1);
    for (int i = 0; i < K1_NST; i++) { mbar_init(barF + 8 * i, 1); mbar_init(barE + 8 * i, 8); }
    fence_barrier_init();
    fence_proxy_async();
    for (int kb = 0; kb < 2; kb++) {
      mbar_expect_tx(barA + 8 * kb, 16384);
      tma_2d(sA + kb * 16384, &tmX, kb * 64, rb * 128, barA + 8 * kb);
    }
  }
  pdl_launch();
  __syncwarp();
  cluster_arrive();
  cluster_wait();

  if (warp < 4) {
    if (warp == 0) {
      if (lane == 0) {
#pragma unroll 1
        for (int it = 0; it < 40; it++) {
          const int st = it & (K1_NST - 1), t = it / 10, kb = it - t * 10;
          if (it >= K1_NST) mbar_wait(barE + 8 * st, ((it / K1_NST) - 1) & 1);
          mbar_expect_tx(barF + 8 * st, 16384);
          const CUtensorMap* m = t < 2 ? &tmWqkv : &tmW1;
          const int col = (t < 2 ? cg * 240 + t * 120 : cg * 216 + (t - 2) * 104) + (int)rank * 64;
          tma_2d_mc(sB + st * 16384 + rank * 8192, m, col, kb * 64, barF + 8 * st, (uint16_t)3);
          if (it < 8) {
            const int ka = it + 2;
            mbar_expect_tx(barA + 8 * ka, 16384);
            tma_2d(sA + ka * 16384, &tmX, ka * 64, rb * 128, barA + 8 * ka);
          }
        }
      }
    } else if (warp == 1) {
      const int r = cg * 16 + (lane >> 1), half = lane & 1;
      float acc = 0.f;
      mbar_wait(barA + 72, 0);
#pragma unroll 1
      for (int kb = half * 5; kb < half * 5 + 5; kb++) {
        mbar_wait(barA + 8 * kb, 0);
#pragma unroll
        for (int c = 0; c < 8; c++) {
          uint4 xv;
          asm volatile("ld.shared.v4.u32 {%0,%1,%2,%3}, [%4];" : "=r"(xv.x), "=r"(xv.y), "=r"(xv.z), "=r"(xv.w)
                       : "r"(sA + kb * 16384 + r * 128 + ((c ^ (r & 7)) << 4)));
          const uint4 wv = __ldg(reinterpret_cast<const uint4*>(gate_w + kb * 64 + c * 8));
          acc = fmaf(bf_lo(xv.x), bf_lo(wv.x), acc); acc = fmaf(bf_hi(xv.x), bf_hi(wv.x), acc);
          acc = fmaf(bf_lo(xv.y), bf_lo(wv.y), acc); acc = fmaf(bf_hi(xv.y), bf_hi(wv.y), acc);
          acc = fmaf(bf_lo(xv.z), bf_lo(wv.z), acc); acc = fmaf(bf_hi(xv.z), bf_hi(wv.z), acc);
          acc = fmaf(bf_lo(xv.w), bf_lo(wv.w), acc); acc = fmaf(bf_hi(xv.w), bf_hi(wv.w), acc);
        }
      }
      acc += __shfl_xor_sync(0xffffffffu, acc, 1);
      if (!half) g_gate[rb * 128 + r] = 1.f / (1.f + __expf(-acc));
    }
  } else {
    const int wgi = (warp >> 2) - 1, wq = warp & 3, g = lane >> 2, t4 = lane & 3;
    const uint32_t barE_self = mapa(barE, rank), barE_peer = mapa(barE, rank ^ 1);
    const bool elect = lane == 0;
    {
      float acc0[60], acc1[60];
      k1_mainloop<120>(acc0, acc1, [](float (&d)[60], uint64_t a, uint64_t b, int sd) { wgmma_ssp_n120_t01(d, a, b, sd); },
                       sA, sB, barA, barF, barE_self, barE_peer, wgi * 10, true, elect, wgi ? 1 : 0, wgi ? 2 : 1);
      if (warp == 4) STAMP(1);
      float nrm[6] = {0.f, 0.f, 0.f, 0.f, 0.f, 0.f};
      const int slot0 = cg * 12 + wgi * 6;
      k1_qkv_epi(acc0, nrm, slot0, rb * 16 + wq * 2, g, t4);
      k1_qkv_epi(acc1, nrm, slot0, rb * 16 + 8 + wq * 2, g, t4);
#pragma unroll
      for (int h = 0; h < 6; h++) {
        const uint32_t m = __reduce_max_sync(0xffffffffu, __float_as_uint(nrm[h]));
        if (lane == h) g_norm[(slot0 + h) * 64 + rb * 4 + wq] = __uint_as_float(m);
      }
    }
    if (warp == 4) STAMP(2);
    {
      float acc0[56], acc1[56];
      k1_mainloop<112>(acc0, acc1, [](float (&d)[56], uint64_t a, uint64_t b, int sd) { wgmma_ssp_n112_t01(d, a, b, sd); },
                       sA, sB, barA, barF, barE_self, barE_peer, 20 + wgi * 10, false, elect, wgi ? 1 : 2, wgi ? 0 : 1);
      if (warp == 8) STAMP(3);
      uint8_t* base = g_A2 + ((size_t)(rb * 296 + cg * 27 + wgi * 13) * 16 + wq * 2) * 128 + g * 16 + t4 * 4;
      const uint32_t* bp = reinterpret_cast<const uint32_t*>(b1 + cg * 216 + wgi * 104 + t4 * 2);
#pragma unroll
      for (int j = 0; j < 14; j++) {
        const uint32_t bv = __ldg(bp + j * 4);
        const float c0 = bf_lo(bv), c1 = bf_hi(bv);
        float h0 = fmaxf(acc0[4 * j] + c0, 0.f), h1 = fmaxf(acc0[4 * j + 1] + c1, 0.f);
        float h2 = fmaxf(acc0[4 * j + 2] + c0, 0.f), h3 = fmaxf(acc0[4 * j + 3] + c1, 0.f);
        st32(base + j * 2048, pack_bf16(h0 * h0, h1 * h1));
        st32(base + j * 2048 + 128, pack_bf16(h2 * h2, h3 * h3));
        h0 = fmaxf(acc1[4 * j] + c0, 0.f); h1 = fmaxf(acc1[4 * j + 1] + c1, 0.f);
        h2 = fmaxf(acc1[4 * j + 2] + c0, 0.f); h3 = fmaxf(acc1[4 * j + 3] + c1, 0.f);
        st32(base + j * 2048 + 1024, pack_bf16(h0 * h0, h1 * h1));
        st32(base + j * 2048 + 1024 + 128, pack_bf16(h2 * h2, h3 * h3));
      }
    }
    if (warp == 8) STAMP(4);
  }
  __syncwarp();
  cluster_arrive_relaxed();
  cluster_wait();
}

constexpr int KV_HEAD_BYTES = 256 * 768, Q_BYTES = 8 * 4096;
constexpr int AT_NCHUNK = 16, AT_CHUNK_BYTES = KV_HEAD_BYTES / AT_NCHUNK;
constexpr int AT_SMEM = KV_HEAD_BYTES + Q_BYTES + 1024 + 1024;

template <int T0, int T1, int TOFF>
__device__ __forceinline__ void exp_tiles(const float (&s)[32], uint32_t (&p)[16], uint32_t cmask, uint32_t cone) {
#pragma unroll
  for (int t = T0; t < T1; t++) {
#pragma unroll
    for (int h = 0; h < 2; h++) {
      const float x0 = s[4 * t + 2 * h], x1 = s[4 * t + 2 * h + 1];
      uint32_t r;
      if ((MUFU_MASK >> ((t + TOFF) & 15)) & 1) {
        r = pack_bf16(ex2(x0), ex2(x1));
      } else {
        const uint32_t u = __byte_perm(__float_as_uint(x0), __float_as_uint(x1), 0x5410);
        uint32_t g;
        asm("lop3.b32 %0, %1, %2, %3, 0xEA;" : "=r"(g) : "r"(u), "r"(cmask), "r"(cone));
        r = hfma2_bf16(g, g, 0x40034003u) + u - g;
      }
      p[2 * t + h] = r;
      asm volatile("" : "+r"(p[2 * t + h])::"memory");
    }
  }
}
template <int TOFF>
__device__ __forceinline__ void exp_pv(const float (&s)[32], uint32_t (&p)[16], float (&o)[12], uint64_t dv, int sd, uint32_t cmask, uint32_t cone) {
  exp_tiles<0, 4, TOFF>(s, p, cmask, cone);
  wg_fence();
  wgmma_rs_n24_t1(o, p[0], p[1], p[2], p[3], dv, sd);
  wgmma_rs_n24_t1(o, p[4], p[5], p[6], p[7], dv + 96, 1);
  exp_tiles<4, 8, TOFF>(s, p, cmask, cone);
  wg_fence();
  wgmma_rs_n24_t1(o, p[8], p[9], p[10], p[11], dv + 192, 1);
  wgmma_rs_n24_t1(o, p[12], p[13], p[14], p[15], dv + 288, 1);
}
__device__ __forceinline__ void qk64(float (&s)[32], uint64_t dq, uint64_t dk) {
  wgmma_ss0_n64_t00(s, dq, dk);
  wgmma_ss_n64_t00(s, dq + 16, dk + 16);
}
__device__ __forceinline__ void attn_store(const float (&o)[12], int row0, int head, int lane) {
  const int t4 = lane & 3;
  const float l0 = __shfl_sync(0xffffffffu, o[8], (lane & ~3) | 2), l1 = __shfl_sync(0xffffffffu, o[10], (lane & ~3) | 2);
  const float r0 = __fdividef(g_gate[row0], l0), r1 = __fdividef(g_gate[row0 + 8], l1);
  uint8_t* base = g_A2 + ((size_t)((row0 >> 7) * 296 + 216) * 16 + ((row0 & 127) >> 3)) * 128 + (row0 & 7) * 16;
#pragma unroll
  for (int tt = 0; tt < 3; tt++) {
    const int d = tt * 8 + 2 * t4;
    if (d < 20) {
      const int col = head * 20 + d;
      uint8_t* ptr = base + (col >> 3) * 2048 + (col & 7) * 2;
      *reinterpret_cast<uint32_t*>(ptr) = pack_bf16(o[4 * tt] * r0, o[4 * tt + 1] * r0);
      *reinterpret_cast<uint32_t*>(ptr + 128) = pack_bf16(o[4 * tt + 2] * r1, o[4 * tt + 3] * r1);
    }
  }
}

__device__ __forceinline__ void attn_slow(uint32_t sb, uint32_t bb, int wg, int rowbase, int head, int lane) {
  const uint64_t dk0 = mk_desc(sb, 128, 768, 0), dv0 = mk_desc(sb + 384, 768, 128, 0);
  const uint64_t dq0 = mk_desc(sb + KV_HEAD_BYTES + wg * 8192, 128, 512, 0);
#pragma unroll 1
  for (int mt = 0; mt < 2; mt++) {
    float o[12], s[32];
    uint32_t p[16];
#pragma unroll
    for (int i = 0; i < 12; i++) o[i] = 0.f;
    float m0 = -INFINITY, m1 = -INFINITY;
#pragma unroll 1
    for (int b = 0; b < 32; b++) {
      if (mt == 0 && !(b & 1)) mbar_wait(bb + 8 * (b >> 1), 0);
      wg_fence();
      qk64(s, dq0 + (uint32_t)(mt * 256), dk0 + (uint32_t)(b * 384));
      wg_commit();
      wg_wait<0>();
      fence_regs(s);
      float n0 = m0, n1 = m1;
#pragma unroll
      for (int t = 0; t < 8; t++) { n0 = fmaxf(n0, fmaxf(s[4 * t], s[4 * t + 1])); n1 = fmaxf(n1, fmaxf(s[4 * t + 2], s[4 * t + 3])); }
      n0 = fmaxf(n0, __shfl_xor_sync(0xffffffffu, n0, 1)); n0 = fmaxf(n0, __shfl_xor_sync(0xffffffffu, n0, 2));
      n1 = fmaxf(n1, __shfl_xor_sync(0xffffffffu, n1, 1)); n1 = fmaxf(n1, __shfl_xor_sync(0xffffffffu, n1, 2));
      const float a0 = ex2(m0 - n0), a1 = ex2(m1 - n1);
      m0 = n0; m1 = n1;
#pragma unroll
      for (int t = 0; t < 3; t++) { o[4 * t] *= a0; o[4 * t + 1] *= a0; o[4 * t + 2] *= a1; o[4 * t + 3] *= a1; }
#pragma unroll
      for (int t = 0; t < 8; t++) {
        p[2 * t] = pack_bf16(ex2(s[4 * t] - m0), ex2(s[4 * t + 1] - m0));
        p[2 * t + 1] = pack_bf16(ex2(s[4 * t + 2] - m1), ex2(s[4 * t + 3] - m1));
      }
      fence_regs(o);
      wg_fence();
#pragma unroll
      for (int k = 0; k < 4; k++) wgmma_rs_n24_t1(o, p[4 * k], p[4 * k + 1], p[4 * k + 2], p[4 * k + 3], dv0 + (uint32_t)(b * 384 + k * 96), 1);
      wg_commit();
      wg_wait<0>();
      fence_regs(o);
    }
    attn_store(o, rowbase + mt * 64, head, lane);
  }
}

__global__ void __launch_bounds__(512, 1) k2_attn(int opaque_zero) {
  extern __shared__ uint8_t smem_raw[];
  const uint32_t sb = (smem_u32(smem_raw) + 1023u) & ~1023u;
  const uint32_t bb = sb + KV_HEAD_BYTES + Q_BYTES;
  const int tid = threadIdx.x, lane = tid & 31;
  const int warp = __shfl_sync(0xffffffffu, tid >> 5, 0), wg = warp >> 2;
  const int head = blockIdx.x >> 2, qb = blockIdx.x & 3;
  if (tid == 0) {
    STAMP(5);
    for (int i = 0; i <= AT_NCHUNK; i++) mbar_init(bb + 8 * i, 1);
    fence_barrier_init();
    fence_proxy_async();
  }
  pdl_launch();
  pdl_wait();
  if (tid == 0) {
    STAMP(6);
    mbar_expect_tx(bb + 8 * AT_NCHUNK, Q_BYTES);
    bulk_g2s(sb + KV_HEAD_BYTES, g_QKV + (size_t)blockIdx.x * Q_BYTES, Q_BYTES, bb + 8 * AT_NCHUNK);
    for (int i = 0; i < AT_NCHUNK; i++) {
      mbar_expect_tx(bb + 8 * i, AT_CHUNK_BYTES);
      bulk_g2s(sb + i * AT_CHUNK_BYTES, g_QKV + KV_OFF + (size_t)head * KV_HEAD_BYTES + i * AT_CHUNK_BYTES, AT_CHUNK_BYTES, bb + 8 * i);
    }
  }
  bool fast;
  {
    const uint32_t* nb = reinterpret_cast<const uint32_t*>(g_norm);
    const uint2 k2 = *reinterpret_cast<const uint2*>(nb + (32 + head) * 64 + lane * 2);
    const uint2 v2 = *reinterpret_cast<const uint2*>(nb + (64 + head) * 64 + lane * 2);
    const float nq = __uint_as_float(__reduce_max_sync(0xffffffffu, nb[head * 64 + qb * 16 + (lane & 15)]));
    const float nk = __uint_as_float(__reduce_max_sync(0xffffffffu, max(k2.x, k2.y)));
    const float nv = __uint_as_float(__reduce_max_sync(0xffffffffu, max(v2.x, v2.y)));
    fast = (nq * nk <= 2304.0f) && (nq <= 1e30f) && (nk <= 1e30f) && (nv <= 1e30f) && (nv >= 1e-18f);
  }
  const int rowbase = qb * 512 + wg * 128 + (warp & 3) * 16 + (lane >> 2);
  __syncthreads();
  mbar_wait(bb + 8 * AT_NCHUNK, 0);
  if (!fast) {
    *reinterpret_cast<uint2*>(smem_raw + (sb - smem_u32(smem_raw)) + KV_HEAD_BYTES + (tid >> 3) * 512 + 256 + (tid & 7) * 16 + 8) = make_uint2(0u, 0u);
    fence_proxy_async();
    __syncthreads();
    attn_slow(sb, bb, wg, rowbase, head, lane);
    return;
  }
  uint32_t cmask = 0x007F007Fu + opaque_zero, cone = 0x3F803F80u + opaque_zero;
  const uint64_t dk0 = mk_desc(sb, 128, 768, 0), dv0 = mk_desc(sb + 384, 768, 128, 0);
  const uint64_t dq0 = mk_desc(sb + KV_HEAD_BYTES + wg * 8192, 128, 512, 0);
  float o[12], s0[32], s1[32];
  uint32_t p0[16], p1[16];
#pragma unroll
  for (int i = 0; i < 12; i++) o[i] = 0.f;
  fence_regs(o);
  mbar_wait(bb, 0);
  wg_fence();
  qk64(s0, dq0, dk0);
  wg_commit();
  wg_wait<0>();
  fence_regs(s0);
#pragma unroll 1
  for (int it = 0; it < 32; it++) {
    const int c = it & 15, mt = it >> 4;
    const uint64_t dq = dq0 + (uint32_t)(mt * 256);
    const uint32_t off = c * 768;
    wg_fence();
    qk64(s1, dq, dk0 + (off + 384));
    wg_commit();
    exp_pv<0>(s0, p0, o, dv0 + off, c, cmask, cone);
    wg_commit();
    wg_wait<1>();
    fence_regs(s1);
    const int cn = (c + 1) & 15;
    const uint64_t dqn = dq0 + (uint32_t)((((it + 1) >> 4) & 1) * 256);
    if (it < 15) mbar_wait(bb + 8 * cn, 0);
    wg_fence();
    qk64(s0, dqn, dk0 + (uint32_t)(cn * 768));
    wg_commit();
    exp_pv<8>(s1, p1, o, dv0 + (off + 384), 1, cmask, cone);
    wg_commit();
    wg_wait<0>();
    fence_regs(s0);
    fence_regs(o);
    if (c == 15) attn_store(o, rowbase + mt * 64, head, lane);
  }
  if (warp == 0) STAMP(8);
}

constexpr int K3_NST = 8, K3_STAGE = 8192 + 10240;
constexpr int K3_RED = 128 * 80 * 4;
constexpr int K3_SMEM = K3_NST * K3_STAGE + K3_RED + 1024 + 1024;

__global__ void __cluster_dims__(2, 1, 1) __launch_bounds__(288, 1)
k3_out(const __grid_constant__ CUtensorMap tmW2, const __grid_constant__ CUtensorMap tmWo, const __nv_bfloat16* __restrict__ b2,
       __nv_bfloat16* __restrict__ out) {
  extern __shared__ uint8_t smem_raw[];
  const uint32_t sb = (smem_u32(smem_raw) + 1023u) & ~1023u;
  const uint32_t sRed = sb + K3_NST * K3_STAGE, barF = sRed + K3_RED, barE = barF + 8 * K3_NST, barR = barE + 8 * K3_NST;
  const int tid = threadIdx.x, lane = tid & 31;
  const int warp = __shfl_sync(0xffffffffu, tid >> 5, 0);
  const uint32_t rank = cluster_rank();
  const int tile = blockIdx.x >> 1, rb = tile >> 2, ct = tile & 3;
  if (tid == 0) {
    STAMP(9);
    prefetch_tmap(&tmW2); prefetch_tmap(&tmWo);
    for (int i = 0; i < K3_NST; i++) { mbar_init(barF + 8 * i, 1); mbar_init(barE + 8 * i, 8); }
    mbar_init(barR, 1);
    fence_barrier_init();
    mbar_expect_tx(barR, K3_RED);
  }
  __syncwarp();
  cluster_arrive();
  cluster_wait();
  if (warp == 8) {
    if (lane == 0) {
      const int s0 = rank * 37;
      const uint8_t* asrc = g_A2 + (size_t)rb * 296 * 2048;
      for (int i = 0; i < K3_NST; i++) {
        const int s = s0 + i;
        mbar_expect_tx(barF + 8 * i, K3_STAGE);
        for (int b = 0; b < 5; b++) tma_2d(sb + i * K3_STAGE + 8192 + b * 2048, &tmW2, ct * 160 + b * 32, s * 32, barF + 8 * i);
      }
      pdl_wait();
      for (int i = 0; i < K3_NST; i++) bulk_g2s(sb + i * K3_STAGE, asrc + (size_t)(s0 + i) * 8192, 8192, barF + 8 * i);
#pragma unroll 1
      for (int i = K3_NST; i < 37; i++) {
        const int st = i & (K3_NST - 1), s = s0 + i;
        mbar_wait(barE + 8 * st, ((i / K3_NST) - 1) & 1);
        mbar_expect_tx(barF + 8 * st, K3_STAGE);
        bulk_g2s(sb + st * K3_STAGE, asrc + (size_t)s * 8192, 8192, barF + 8 * st);
        const CUtensorMap* m = s < 54 ? &tmW2 : &tmWo;
        const int k = (s < 54 ? s : s - 54) * 32;
        for (int b = 0; b < 5; b++) tma_2d(sb + st * K3_STAGE + 8192 + b * 2048, m, ct * 160 + b * 32, k, barF + 8 * st);
      }
    }
  } else {
    const int wgi = warp >> 2, wq = warp & 3, g = lane >> 2, t4 = lane & 3;
    const int rloc = wgi * 64 + wq * 16 + g, row = rb * 128 + rloc;
    pdl_wait();
    if (warp == 0) STAMP(10);
    const float w0 = 1.f - g_gate[row], w1 = 1.f - g_gate[row + 8];
    float acc[80];
    const uint64_t dA0 = mk_desc(sb + wgi * 1024, 2048, 128, 0), dB0 = mk_desc(sb + 8192, 2048, 512, 2);
    const int nsw = rank ? 17 : 37;
    fence_regs(acc);
#pragma unroll 1
    for (int i = 0; i < 37; i++) {
      const int st = i & (K3_NST - 1);
      mbar_wait(barF + 8 * st, (i / K3_NST) & 1);
      const uint32_t off = st * (K3_STAGE >> 4);
      wg_fence();
      wgmma_ssp_n160_t01(acc, dA0 + off, dB0 + off, i);
      wgmma_ssp_n160_t01(acc, dA0 + off + 256, dB0 + off + 64, 1);
      wg_commit();
      if (i + 1 == nsw) {
        wg_wait<0>();
        fence_regs(acc);
#pragma unroll
        for (int j = 0; j < 20; j++) { acc[4 * j] *= w0; acc[4 * j + 1] *= w0; acc[4 * j + 2] *= w1; acc[4 * j + 3] *= w1; }
        fence_regs(acc);
      } else {
        wg_wait<1>();
      }
      if (i > 0 && lane == 0) mbar_arrive(barE + 8 * ((i - 1) & (K3_NST - 1)));
    }
    wg_wait<0>();
    fence_regs(acc);
    if (warp == 0) STAMP(11);
    const uint32_t peerRed = mapa(sRed, rank ^ 1) + tid * 16, peerBar = mapa(barR, rank ^ 1);
#pragma unroll
    for (int j = 0; j < 10; j++) {
      const float a0 = rank ? acc[4 * j] : acc[40 + 4 * j], a1 = rank ? acc[4 * j + 1] : acc[40 + 4 * j + 1];
      const float a2 = rank ? acc[4 * j + 2] : acc[40 + 4 * j + 2], a3 = rank ? acc[4 * j + 3] : acc[40 + 4 * j + 3];
      asm volatile("st.async.weak.shared::cluster.mbarrier::complete_tx::bytes.v4.f32 [%0], {%1, %2, %3, %4}, [%5];"
                   ::"r"(peerRed + j * 4096), "f"(a0), "f"(a1), "f"(a2), "f"(a3), "r"(peerBar) : "memory");
    }
    const int col0 = ct * 160 + rank * 80 + t4 * 2;
    mbar_wait(barR, 0);
#pragma unroll
    for (int j = 0; j < 10; j++) {
      float p0, p1, p2, p3;
      asm volatile("ld.shared.v4.f32 {%0, %1, %2, %3}, [%4];" : "=f"(p0), "=f"(p1), "=f"(p2), "=f"(p3) : "r"(sRed + tid * 16 + j * 4096));
      const float a0 = rank ? acc[40 + 4 * j] : acc[4 * j], a1 = rank ? acc[40 + 4 * j + 1] : acc[4 * j + 1];
      const float a2 = rank ? acc[40 + 4 * j + 2] : acc[4 * j + 2], a3 = rank ? acc[40 + 4 * j + 3] : acc[4 * j + 3];
      const uint32_t bv = __ldg(reinterpret_cast<const uint32_t*>(b2 + col0 + j * 8));
      const float c0 = bf_lo(bv), c1 = bf_hi(bv);
      *reinterpret_cast<uint32_t*>(out + (size_t)row * D_ + col0 + j * 8) = pack_bf16(fmaf(w0, c0, a0 + p0), fmaf(w0, c1, a1 + p1));
      *reinterpret_cast<uint32_t*>(out + (size_t)(row + 8) * D_ + col0 + j * 8) = pack_bf16(fmaf(w1, c0, a2 + p2), fmaf(w1, c1, a3 + p3));
    }
    if (warp == 0) STAMP(12);
  }
}

typedef CUresult (*EncodeFn)(CUtensorMap*, CUtensorMapDataType, cuuint32_t, void*, const cuuint64_t*, const cuuint64_t*, const cuuint32_t*,
                             const cuuint32_t*, CUtensorMapInterleave, CUtensorMapSwizzle, CUtensorMapL2promotion, CUtensorMapFloatOOBfill);

void make_map(EncodeFn fn, CUtensorMap* m, const void* ptr, uint64_t inner, uint64_t outer, uint32_t box_inner, uint32_t box_outer, CUtensorMapSwizzle sw) {
  cuuint64_t dims[2] = {inner, outer};
  cuuint64_t strides[1] = {inner * 2};
  cuuint32_t box[2] = {box_inner, box_outer};
  cuuint32_t es[2] = {1, 1};
  fn(m, CU_TENSOR_MAP_DATA_TYPE_BFLOAT16, 2, const_cast<void*>(ptr), dims, strides, box, es, CU_TENSOR_MAP_INTERLEAVE_NONE, sw,
     CU_TENSOR_MAP_L2_PROMOTION_L2_256B, CU_TENSOR_MAP_FLOAT_OOB_FILL_NONE);
}

}

extern "C" void kernel_launch(void* const* d_in, const int* in_sizes, int n_in, void* d_out, int out_size) {
  (void)in_sizes; (void)n_in; (void)out_size;
  const __nv_bfloat16* x = (const __nv_bfloat16*)d_in[0];
  const __nv_bfloat16* wqkv = (const __nv_bfloat16*)d_in[1];
  const __nv_bfloat16* wo = (const __nv_bfloat16*)d_in[2];
  const __nv_bfloat16* w1 = (const __nv_bfloat16*)d_in[4];
  const __nv_bfloat16* b1 = (const __nv_bfloat16*)d_in[5];
  const __nv_bfloat16* w2 = (const __nv_bfloat16*)d_in[6];
  const __nv_bfloat16* b2 = (const __nv_bfloat16*)d_in[7];
  const __nv_bfloat16* gw = (const __nv_bfloat16*)d_in[8];

  static EncodeFn enc = nullptr;
  if (!enc) {
    void* p = nullptr;
    cudaDriverEntryPointQueryResult qr;
    cudaGetDriverEntryPoint("cuTensorMapEncodeTiled", &p, cudaEnableDefault, &qr);
    enc = (EncodeFn)p;
    cudaFuncSetAttribute(k1_proj, cudaFuncAttributeMaxDynamicSharedMemorySize, K1_SMEM);
    cudaFuncSetAttribute(k2_attn, cudaFuncAttributeMaxDynamicSharedMemorySize, AT_SMEM);
    cudaFuncSetAttribute(k3_out, cudaFuncAttributeMaxDynamicSharedMemorySize, K3_SMEM);
  }
  CUtensorMap tmX, tmWqkv, tmW1, tmW2, tmWo;
  make_map(enc, &tmX, x, D_, S_, 64, 128, CU_TENSOR_MAP_SWIZZLE_128B);
  make_map(enc, &tmWqkv, wqkv, 3 * D_, D_, 64, 64, CU_TENSOR_MAP_SWIZZLE_128B);
  make_map(enc, &tmW1, w1, F_, D_, 64, 64, CU_TENSOR_MAP_SWIZZLE_128B);
  make_map(enc, &tmW2, w2, D_, F_, 32, 32, CU_TENSOR_MAP_SWIZZLE_64B);
  make_map(enc, &tmWo, wo, D_, D_, 32, 32, CU_TENSOR_MAP_SWIZZLE_64B);

  cudaStream_t st = cudaStreamPerThread;
  k1_proj<<<128, 384, K1_SMEM, st>>>(tmX, tmWqkv, tmW1, b1, gw);

  cudaLaunchAttribute at[1];
  at[0].id = cudaLaunchAttributeProgrammaticStreamSerialization;
  at[0].val.programmaticStreamSerializationAllowed = 1;
  {
    cudaLaunchConfig_t cfg = {};
    cfg.gridDim = dim3(128); cfg.blockDim = dim3(512); cfg.dynamicSmemBytes = AT_SMEM; cfg.stream = st;
    cfg.attrs = at; cfg.numAttrs = 1;
    cudaLaunchKernelEx(&cfg, k2_attn, 0);
  }
  {
    cudaLaunchConfig_t cfg = {};
    cfg.gridDim = dim3(128); cfg.blockDim = dim3(288); cfg.dynamicSmemBytes = K3_SMEM; cfg.stream = st;
    cfg.attrs = at; cfg.numAttrs = 1;
    cudaLaunchKernelEx(&cfg, k3_out, tmW2, tmWo, b2, (__nv_bfloat16*)d_out);
  }
}
```

```cpp
#include <cuda_runtime.h>
#include <cuda_bf16.h>
#include <cuda.h>
#include <stdint.h>

namespace {

constexpr int S_ = 2048, D_ = 640, NH = 32, F_ = 1728;

constexpr uint32_t KV_OFF = NH * 256 * 512;
__device__ __align__(1024) uint8_t g_QKV[NH * 256 * 512 + NH * 256 * 768];
__device__ __align__(1024) uint8_t g_A2[16 * 296 * 2048];
__device__ float g_gate[S_];
__device__ float g_norm[96 * 64];

constexpr uint32_t MUFU_MASK = 0x5151u;

#define STAMP(i) do { } while (0)

__device__ __forceinline__ uint32_t smem_u32(const void* p) { return (uint32_t)__cvta_generic_to_shared(p); }
__device__ __forceinline__ void wg_fence() { asm volatile("wgmma.fence.sync.aligned;" ::: "memory"); }
__device__ __forceinline__ void wg_commit() { asm volatile("wgmma.commit_group.sync.aligned;" ::: "memory"); }
template <int N> __device__ __forceinline__ void wg_wait() { asm volatile("wgmma.wait_group.sync.aligned %0;" ::"n"(N) : "memory"); }
template <int N> __device__ __forceinline__ void fence_regs(float (&r)[N]) {
#pragma unroll
  for (int i = 0; i < N; i++) asm volatile("" : "+f"(r[i])::"memory");
}
__device__ __forceinline__ float ex2(float x) { float y; asm("ex2.approx.ftz.f32 %0, %1;" : "=f"(y) : "f"(x)); return y; }
__device__ __forceinline__ uint32_t pack_bf16(float lo, float hi) { uint32_t y; asm("cvt.rn.bf16x2.f32 %0, %1, %2;" : "=r"(y) : "f"(hi), "f"(lo)); return y; }
__device__ __forceinline__ uint32_t hfma2_bf16(uint32_t a, uint32_t b, uint32_t c) { uint32_t y; asm("fma.rn.bf16x2 %0, %1, %2, %3;" : "=r"(y) : "r"(a), "r"(b), "r"(c)); return y; }
__device__ __forceinline__ float bf_lo(uint32_t v) { return __uint_as_float(v << 16); }
__device__ __forceinline__ float bf_hi(uint32_t v) { return __uint_as_float(v & 0xffff0000u); }
__device__ __forceinline__ void mbar_init(uint32_t bar, int cnt) { asm volatile("mbarrier.init.shared::cta.b64 [%0], %1;" ::"r"(bar), "r"(cnt)); }
__device__ __forceinline__ void mbar_expect_tx(uint32_t bar, uint32_t bytes) { asm volatile("mbarrier.arrive.expect_tx.shared::cta.b64 _, [%0], %1;" ::"r"(bar), "r"(bytes) : "memory"); }
__device__ __forceinline__ void mbar_arrive(uint32_t bar) { asm volatile("mbarrier.arrive.shared::cta.b64 _, [%0];" ::"r"(bar) : "memory"); }
__device__ __forceinline__ void mbar_arrive_cluster(uint32_t cluster_addr) { asm volatile("mbarrier.arrive.shared::cluster.b64 _, [%0];" ::"r"(cluster_addr) : "memory"); }
__device__ __forceinline__ void mbar_wait(uint32_t bar, uint32_t parity) {
  asm volatile(
      "{\n.reg .pred p;\n.reg .u32 n;\n"
      "mbarrier.try_wait.parity.shared::cta.b64 p, [%0], %1;\n"
      "@p bra DONE;\n"
      "mov.u32 n, 0;\n"
      "LOOP:\n"
      "mbarrier.try_wait.parity.shared::cta.b64 p, [%0], %1;\n"
      "@p bra DONE;\n"
      "add.u32 n, n, 1;\n"
      "setp.lt.u32 p, n, 0x1000000;\n"
      "@p bra LOOP;\n"
      "trap;\n"
      "DONE:\n}\n" ::"r"(bar), "r"(parity) : "memory");
}
__device__ __forceinline__ void bulk_g2s(uint32_t dst, const void* src, uint32_t bytes, uint32_t bar) {
  asm volatile("cp.async.bulk.shared::cluster.global.mbarrier::complete_tx::bytes [%0], [%1], %2, [%3];" ::"r"(dst), "l"(src), "r"(bytes), "r"(bar) : "memory");
}
__device__ __forceinline__ void tma_2d(uint32_t dst, const CUtensorMap* m, int c0, int c1, uint32_t bar) {
  asm volatile("cp.async.bulk.tensor.2d.shared::cluster.global.mbarrier::complete_tx::bytes [%0], [%1, {%3, %4}], [%2];" ::"r"(dst), "l"(m), "r"(bar), "r"(c0), "r"(c1) : "memory");
}
__device__ __forceinline__ void tma_2d_mc(uint32_t dst, const CUtensorMap* m, int c0, int c1, uint32_t bar, uint16_t mask) {
  asm volatile("cp.async.bulk.tensor.2d.shared::cluster.global.mbarrier::complete_tx::bytes.multicast::cluster [%0], [%1, {%3, %4}], [%2], %5;" ::"r"(dst), "l"(m), "r"(bar), "r"(c0), "r"(c1), "h"(mask) : "memory");
}
__device__ __forceinline__ uint32_t mapa(uint32_t addr, uint32_t rank) { uint32_t r; asm("mapa.shared::cluster.u32 %0, %1, %2;" : "=r"(r) : "r"(addr), "r"(rank)); return r; }
__device__ __forceinline__ uint32_t cluster_rank() { uint32_t r; asm("mov.u32 %0, %%cluster_ctarank;" : "=r"(r)); return r; }
__device__ __forceinline__ void cluster_arrive() { asm volatile("barrier.cluster.arrive.release.aligned;" ::: "memory"); }
__device__ __forceinline__ void cluster_arrive_relaxed() { asm volatile("barrier.cluster.arrive.relaxed.aligned;" ::: "memory"); }
__device__ __forceinline__ void cluster_wait() { asm volatile("barrier.cluster.wait.acquire.aligned;" ::: "memory"); }
__device__ __forceinline__ void bar_sync(int id, int n) { asm volatile("bar.sync %0, %1;" ::"r"(id), "r"(n) : "memory"); }
__device__ __forceinline__ void bar_arrive(int id, int n) { asm volatile("bar.arrive %0, %1;" ::"r"(id), "r"(n) : "memory"); }
__device__ __forceinline__ void pdl_launch() { asm volatile("griddepcontrol.launch_dependents;" ::: "memory"); }
__device__ __forceinline__ void pdl_wait() { asm volatile("griddepcontrol.wait;" ::: "memory"); }
__device__ __forceinline__ void fence_barrier_init() { asm volatile("fence.mbarrier_init.release.cluster;" ::: "memory"); }
__device__ __forceinline__ void fence_proxy_async() { asm volatile("fence.proxy.async.shared::cta;" ::: "memory"); }
__device__ __forceinline__ void prefetch_tmap(const CUtensorMap* m) { asm volatile("prefetch.tensormap [%0];" ::"l"(m) : "memory"); }
__device__ __forceinline__ uint64_t mk_desc(uint32_t addr, uint32_t lbo, uint32_t sbo, uint32_t mode) {
  return (uint64_t)((addr & 0x3FFFF) >> 4) | ((uint64_t)(lbo >> 4) << 16) | ((uint64_t)(sbo >> 4) << 32) | ((uint64_t)mode << 62);
}

__device__ __forceinline__ void wgmma_ssp_n120_t01(float (&d)[60], uint64_t da, uint64_t db, int sd) {
  asm volatile("{\n.reg .pred p;\nsetp.ne.b32 p, %62, 0;\n"
    "wgmma.mma_async.sync.aligned.m64n120k16.f32.bf16.bf16 {%0, %1, %2, %3, %4, %5, %6, %7, %8, %9, %10, %11, %12, %13, %14, %15, %16, %17, %18, %19, %20, %21, %22, %23, %24, %25, %26, %27, %28, %29, %30, %31, %32, %33, %34, %35, %36, %37, %38, %39, %40, %41, %42, %43, %44, %45, %46, %47, %48, %49, %50, %51, %52, %53, %54, %55, %56, %57, %58, %59}, %60, %61, p, 1, 1, 0, 1;\n}\n"
    : "+f"(d[0]), "+f"(d[1]), "+f"(d[2]), "+f"(d[3]), "+f"(d[4]), "+f"(d[5]), "+f"(d[6]), "+f"(d[7]), "+f"(d[8]), "+f"(d[9]), "+f"(d[10]), "+f"(d[11]), "+f"(d[12]), "+f"(d[13]), "+f"(d[14]), "+f"(d[15]), "+f"(d[16]), "+f"(d[17]), "+f"(d[18]), "+f"(d[19]), "+f"(d[20]), "+f"(d[21]), "+f"(d[22]), "+f"(d[23]), "+f"(d[24]), "+f"(d[25]), "+f"(d[26]), "+f"(d[27]), "+f"(d[28]), "+f"(d[29]), "+f"(d[30]), "+f"(d[31]), "+f"(d[32]), "+f"(d[33]), "+f"(d[34]), "+f"(d[35]), "+f"(d[36]), "+f"(d[37]), "+f"(d[38]), "+f"(d[39]), "+f"(d[40]), "+f"(d[41]), "+f"(d[42]), "+f"(d[43]), "+f"(d[44]), "+f"(d[45]), "+f"(d[46]), "+f"(d[47]), "+f"(d[48]), "+f"(d[49]), "+f"(d[50]), "+f"(d[51]), "+f"(d[52]), "+f"(d[53]), "+f"(d[54]), "+f"(d[55]), "+f"(d[56]), "+f"(d[57]), "+f"(d[58]), "+f"(d[59])
    : "l"(da), "l"(db), "r"(sd));
}
__device__ __forceinline__ void wgmma_ssp_n112_t01(float (&d)[56], uint64_t da, uint64_t db, int sd) {
  asm volatile("{\n.reg .pred p;\nsetp.ne.b32 p, %58, 0;\n"
    "wgmma.mma_async.sync.aligned.m64n112k16.f32.bf16.bf16 {%0, %1, %2, %3, %4, %5, %6, %7, %8, %9, %10, %11, %12, %13, %14, %15, %16, %17, %18, %19, %20, %21, %22, %23, %24, %25, %26, %27, %28, %29, %30, %31, %32, %33, %34, %35, %36, %37, %38, %39, %40, %41, %42, %43, %44, %45, %46, %47, %48, %49, %50, %51, %52, %53, %54, %55}, %56, %57, p, 1, 1, 0, 1;\n}\n"
    : "+f"(d[0]), "+f"(d[1]), "+f"(d[2]), "+f"(d[3]), "+f"(d[4]), "+f"(d[5]), "+f"(d[6]), "+f"(d[7]), "+f"(d[8]), "+f"(d[9]), "+f"(d[10]), "+f"(d[11]), "+f"(d[12]), "+f"(d[13]), "+f"(d[14]), "+f"(d[15]), "+f"(d[16]), "+f"(d[17]), "+f"(d[18]), "+f"(d[19]), "+f"(d[20]), "+f"(d[21]), "+f"(d[22]), "+f"(d[23]), "+f"(d[24]), "+f"(d[25]), "+f"(d[26]), "+f"(d[27]), "+f"(d[28]), "+f"(d[29]), "+f"(d[30]), "+f"(d[31]), "+f"(d[32]), "+f"(d[33]), "+f"(d[34]), "+f"(d[35]), "+f"(d[36]), "+f"(d[37]), "+f"(d[38]), "+f"(d[39]), "+f"(d[40]), "+f"(d[41]), "+f"(d[42]), "+f"(d[43]), "+f"(d[44]), "+f"(d[45]), "+f"(d[46]), "+f"(d[47]), "+f"(d[48]), "+f"(d[49]), "+f"(d[50]), "+f"(d[51]), "+f"(d[52]), "+f"(d[53]), "+f"(d[54]), "+f"(d[55])
    : "l"(da), "l"(db), "r"(sd));
}
__device__ __forceinline__ void wgmma_ssp_n160_t01(float (&d)[80], uint64_t da, uint64_t db, int sd) {
  asm volatile("{\n.reg .pred p;\nsetp.ne.b32 p, %82, 0;\n"
    "wgmma.mma_async.sync.aligned.m64n160k16.f32.bf16.bf16 {%0, %1, %2, %3, %4, %5, %6, %7, %8, %9, %10, %11, %12, %13, %14, %15, %16, %17, %18, %19, %20, %21, %22, %23, %24, %25, %26, %27, %28, %29, %30, %31, %32, %33, %34, %35, %36, %37, %38, %39, %40, %41, %42, %43, %44, %45, %46, %47, %48, %49, %50, %51, %52, %53, %54, %55, %56, %57, %58, %59, %60, %61, %62, %63, %64, %65, %66, %67, %68, %69, %70, %71, %72, %73, %74, %75, %76, %77, %78, %79}, %80, %81, p, 1, 1, 0, 1;\n}\n"
    : "+f"(d[0]), "+f"(d[1]), "+f"(d[2]), "+f"(d[3]), "+f"(d[4]), "+f"(d[5]), "+f"(d[6]), "+f"(d[7]), "+f"(d[8]), "+f"(d[9]), "+f"(d[10]), "+f"(d[11]), "+f"(d[12]), "+f"(d[13]), "+f"(d[14]), "+f"(d[15]), "+f"(d[16]), "+f"(d[17]), "+f"(d[18]), "+f"(d[19]), "+f"(d[20]), "+f"(d[21]), "+f"(d[22]), "+f"(d[23]), "+f"(d[24]), "+f"(d[25]), "+f"(d[26]), "+f"(d[27]), "+f"(d[28]), "+f"(d[29]), "+f"(d[30]), "+f"(d[31]), "+f"(d[32]), "+f"(d[33]), "+f"(d[34]), "+f"(d[35]), "+f"(d[36]), "+f"(d[37]), "+f"(d[38]), "+f"(d[39]), "+f"(d[40]), "+f"(d[41]), "+f"(d[42]), "+f"(d[43]), "+f"(d[44]), "+f"(d[45]), "+f"(d[46]), "+f"(d[47]), "+f"(d[48]), "+f"(d[49]), "+f"(d[50]), "+f"(d[51]), "+f"(d[52]), "+f"(d[53]), "+f"(d[54]), "+f"(d[55]), "+f"(d[56]), "+f"(d[57]), "+f"(d[58]), "+f"(d[59]), "+f"(d[60]), "+f"(d[61]), "+f"(d[62]), "+f"(d[63]), "+f"(d[64]), "+f"(d[65]), "+f"(d[66]), "+f"(d[67]), "+f"(d[68]), "+f"(d[69]), "+f"(d[70]), "+f"(d[71]), "+f"(d[72]), "+f"(d[73]), "+f"(d[74]), "+f"(d[75]), "+f"(d[76]), "+f"(d[77]), "+f"(d[78]), "+f"(d[79])
    : "l"(da), "l"(db), "r"(sd));
}
__device__ __forceinline__ void wgmma_ss_n64_t00(float (&d)[32], uint64_t da, uint64_t db) {
  asm volatile("{\n.reg .pred p;\nsetp.ne.b32 p, 1, 0;\n"
    "wgmma.mma_async.sync.aligned.m64n64k16.f32.bf16.bf16 {%0, %1, %2, %3, %4, %5, %6, %7, %8, %9, %10, %11, %12, %13, %14, %15, %16, %17, %18, %19, %20, %21, %22, %23, %24, %25, %26, %27, %28, %29, %30, %31}, %32, %33, p, 1, 1, 0, 0;\n}\n"
    : "+f"(d[0]), "+f"(d[1]), "+f"(d[2]), "+f"(d[3]), "+f"(d[4]), "+f"(d[5]), "+f"(d[6]), "+f"(d[7]), "+f"(d[8]), "+f"(d[9]), "+f"(d[10]), "+f"(d[11]), "+f"(d[12]), "+f"(d[13]), "+f"(d[14]), "+f"(d[15]), "+f"(d[16]), "+f"(d[17]), "+f"(d[18]), "+f"(d[19]), "+f"(d[20]), "+f"(d[21]), "+f"(d[22]), "+f"(d[23]), "+f"(d[24]), "+f"(d[25]), "+f"(d[26]), "+f"(d[27]), "+f"(d[28]), "+f"(d[29]), "+f"(d[30]), "+f"(d[31])
    : "l"(da), "l"(db));
}
__device__ __forceinline__ void wgmma_ss0_n64_t00(float (&d)[32], uint64_t da, uint64_t db) {
  asm volatile("{\n.reg .pred p;\nsetp.ne.b32 p, 0, 0;\n"
    "wgmma.mma_async.sync.aligned.m64n64k16.f32.bf16.bf16 {%0, %1, %2, %3, %4, %5, %6, %7, %8, %9, %10, %11, %12, %13, %14, %15, %16, %17, %18, %19, %20, %21, %22, %23, %24, %25, %26, %27, %28, %29, %30, %31}, %32, %33, p, 1, 1, 0, 0;\n}\n"
    : "=f"(d[0]), "=f"(d[1]), "=f"(d[2]), "=f"(d[3]), "=f"(d[4]), "=f"(d[5]), "=f"(d[6]), "=f"(d[7]), "=f"(d[8]), "=f"(d[9]), "=f"(d[10]), "=f"(d[11]), "=f"(d[12]), "=f"(d[13]), "=f"(d[14]), "=f"(d[15]), "=f"(d[16]), "=f"(d[17]), "=f"(d[18]), "=f"(d[19]), "=f"(d[20]), "=f"(d[21]), "=f"(d[22]), "=f"(d[23]), "=f"(d[24]), "=f"(d[25]), "=f"(d[26]), "=f"(d[27]), "=f"(d[28]), "=f"(d[29]), "=f"(d[30]), "=f"(d[31])
    : "l"(da), "l"(db));
}
__device__ __forceinline__ void wgmma_rs_n24_t1(float (&d)[12], uint32_t a0, uint32_t a1, uint32_t a2, uint32_t a3, uint64_t db, int sd) {
  asm volatile("{\n.reg .pred p;\nsetp.ne.b32 p, %17, 0;\n"
    "wgmma.mma_async.sync.aligned.m64n24k16.f32.bf16.bf16 {%0, %1, %2, %3, %4, %5, %6, %7, %8, %9, %10, %11}, {%12, %13, %14, %15}, %16, p, 1, 1, 1;\n}\n"
    : "+f"(d[0]), "+f"(d[1]), "+f"(d[2]), "+f"(d[3]), "+f"(d[4]), "+f"(d[5]), "+f"(d[6]), "+f"(d[7]), "+f"(d[8]), "+f"(d[9]), "+f"(d[10]), "+f"(d[11])
    : "r"(a0), "r"(a1), "r"(a2), "r"(a3), "l"(db), "r"(sd));
}

constexpr int K1_NST = 8;
constexpr int K1_A_BYTES = 10 * 16384;
constexpr int K1_SMEM = K1_A_BYTES + K1_NST * 8192 + 1024 + 1024;

template <int BN, typename MMA>
__device__ __forceinline__ void k1_mainloop(float (&acc0)[BN / 2], float (&acc1)[BN / 2], MMA mma, uint32_t sA, uint32_t sB, uint32_t barA,
                                            uint32_t barF, uint32_t barE, uint32_t barE_peer, int it0, bool waitA, bool elect, int turn_wait, int turn_give) {
  const uint64_t dA0 = mk_desc(sA, 16, 1024, 1);
  const uint64_t dB0 = mk_desc(sB, 4096, 1024, 1);
  fence_regs(acc0); fence_regs(acc1);
  if (turn_wait) bar_sync(turn_wait, 256);
#pragma unroll 1
  for (int s = 0; s < 20; s++) {
    const int it = it0 + s, st = it & (K1_NST - 1);
    if (waitA && !(s & 1)) mbar_wait(barA + 8 * (s >> 1), 0);
    mbar_wait(barF + 8 * st, (it / K1_NST) & 1);
    const uint64_t da = dA0 + (uint32_t)((s >> 1) * 1024 + (s & 1) * 4);
    const uint64_t db = dB0 + (uint32_t)(st * 512);
    wg_fence();
    mma(acc0, da, db, s);
    mma(acc1, da + 512, db, s);
    mma(acc0, da + 2, db + 128, 1);
    mma(acc1, da + 514, db + 128, 1);
    wg_commit();
    if (s > 0) {
      wg_wait<1>();
      if (elect) { const int ps = (it - 1) & (K1_NST - 1); mbar_arrive_cluster(barE + 8 * ps); mbar_arrive_cluster(barE_peer + 8 * ps); }
    }
  }
  if (turn_give) bar_arrive(turn_give, 256);
  wg_wait<0>();
  fence_regs(acc0); fence_regs(acc1);
  if (elect) { const int ps = (it0 + 19) & (K1_NST - 1); mbar_arrive_cluster(barE + 8 * ps); mbar_arrive_cluster(barE_peer + 8 * ps); }
}

__device__ __forceinline__ void st32(uint8_t* p, uint32_t v) { *reinterpret_cast<uint32_t*>(p) = v; }

__device__ __forceinline__ void k1_qkv_epi(const float (&acc)[60], float (&nrm)[6], int slot0, int grp, int g, int t4) {
  const uint32_t tq = grp * 512 + g * 16, tkv = KV_OFF + grp * 768 + g * 16;
  const bool lo2 = t4 < 2;
  const uint32_t e0 = t4 * 4, e2 = lo2 ? 8 + t4 * 4 : 128 + (t4 - 2) * 4;
  const bool poly0 = !((MUFU_MASK >> (grp & 15)) & 1), poly1 = !((MUFU_MASK >> ((grp + 1) & 15)) & 1);
#pragma unroll
  for (int hp = 0; hp < 3; hp++) {
    uint8_t* ptr[2]; uint32_t gs[2]; float sc[2];
#pragma unroll
    for (int e = 0; e < 2; e++) {
      const int slot = slot0 + 2 * hp + e, which = slot >> 5, head = slot & 31;
      gs[e] = which == 0 ? 512u : 768u;
      sc[e] = which == 0 ? 0.32259642f : 1.0f;
      ptr[e] = g_QKV + (which == 0 ? head * 131072u + tq : head * 196608u + (which == 2 ? 384u : 0u) + tkv);
      if (t4 == 0) {
        uint2 c0, c1;
        if (which == 0) { c0 = make_uint2(0x42FB47C0u, 0x0000BDCCu); c1 = c0; }
        else if (which == 1) { c0 = poly0 ? make_uint2(0x3F803F80u, 0x00003F80u) : make_uint2(0u, 0u);
                               c1 = poly1 ? make_uint2(0x3F803F80u, 0x00003F80u) : make_uint2(0u, 0u); }
        else { c0 = make_uint2(0x00003F80u, 0u); c1 = c0; }
        *reinterpret_cast<uint2*>(ptr[e] + 264) = c0;
        *reinterpret_cast<uint2*>(ptr[e] + 264 + gs[e]) = c1;
      } else if (which == 0 && t4 < 3) {
        *reinterpret_cast<uint4*>(ptr[e] + 384 + (t4 - 1) * 512) = make_uint4(0, 0, 0, 0);
      }
    }
    const float scm = lo2 ? sc[0] : sc[1];
    uint8_t* pm = lo2 ? ptr[0] + 256 + e0 : ptr[1] + (e0 - 8);
    const uint32_t gm = lo2 ? gs[0] : gs[1];
    float q[5][2];
#pragma unroll
    for (int jj = 0; jj < 5; jj++) {
      const int j = hp * 5 + jj;
      const float f = jj < 2 ? sc[0] : (jj == 2 ? scm : sc[1]);
      const float v0 = acc[4 * j] * f, v1 = acc[4 * j + 1] * f, v2 = acc[4 * j + 2] * f, v3 = acc[4 * j + 3] * f;
      uint8_t* p = jj < 2 ? ptr[0] + jj * 128 + e0 : (jj == 2 ? pm : ptr[1] + (jj - 3) * 128 + e2);
      const uint32_t gg = jj < 2 ? gs[0] : (jj == 2 ? gm : gs[1]);
      st32(p, pack_bf16(v0, v1));
      st32(p + gg, pack_bf16(v2, v3));
      q[jj][0] = fmaf(v0, v0, v1 * v1);
      q[jj][1] = fmaf(v2, v2, v3 * v3);
    }
#pragma unroll
    for (int r = 0; r < 2; r++) {
      float a = q[0][r] + q[1][r] + (lo2 ? q[2][r] : 0.f), b = q[3][r] + q[4][r] + (lo2 ? 0.f : q[2][r]);
      a += __shfl_xor_sync(0xffffffffu, a, 1); b += __shfl_xor_sync(0xffffffffu, b, 1);
      a += __shfl_xor_sync(0xffffffffu, a, 2); b += __shfl_xor_sync(0xffffffffu, b, 2);
      nrm[2 * hp] = __uint_as_float(max(__float_as_uint(nrm[2 * hp]), __float_as_uint(a)));
      nrm[2 * hp + 1] = __uint_as_float(max(__float_as_uint(nrm[2 * hp + 1]), __float_as_uint(b)));
    }
  }
}

__global__ void __cluster_dims__(2, 1, 1) __launch_bounds__(384, 1)
k1_proj(const __grid_constant__ CUtensorMap tmX, const __grid_constant__ CUtensorMap tmWqkv, const __grid_constant__ CUtensorMap tmW1,
        const __nv_bfloat16* __restrict__ b1, const __nv_bfloat16* __restrict__ gate_w) {
  extern __shared__ uint8_t smem_raw[];
  const uint32_t sb = (smem_u32(smem_raw) + 1023u) & ~1023u;
  const uint32_t sA = sb, sB = sb + K1_A_BYTES, bars = sB + K1_NST * 8192;
  const uint32_t barA = bars, barF = bars + 80, barE = barF + 8 * K1_NST;
  const int tid = threadIdx.x, lane = tid & 31;
  const int warp = __shfl_sync(0xffffffffu, tid >> 5, 0);
  const int rb = blockIdx.x & 15, cg = blockIdx.x >> 4;
  const uint32_t rank = cluster_rank();
  if (tid == 0) {
    STAMP(0);
    prefetch_tmap(&tmX); prefetch_tmap(&tmWqkv); prefetch_tmap(&tmW1);
    for (int i = 0; i < 10; i++) mbar_init(barA + 8 * i, 1);
    for (int i = 0; i < K1_NST; i++) { mbar_init(barF + 8 * i, 1); mbar_init(barE + 8 * i, 8); }
    fence_barrier_init();
    fence_proxy_async();
    for (int kb = 0; kb < 2; kb++) {
      mbar_expect_tx(barA + 8 * kb, 16384);
      tma_2d(sA + kb * 16384, &tmX, kb * 64, rb * 128, barA + 8 * kb);
    }
  }
  pdl_launch();
  __syncwarp();
  cluster_arrive();
  cluster_wait();

  if (warp < 4) {
    if (warp == 0) {
      if (lane == 0) {
#pragma unroll 1
        for (int it = 0; it < 80; it++) {
          const int st = it & (K1_NST - 1), t = it / 20, ks = it - t * 20;
          if (it >= K1_NST) mbar_wait(barE + 8 * st, ((it / K1_NST) - 1) & 1);
          mbar_expect_tx(barF + 8 * st, 8192);
          const CUtensorMap* m = t < 2 ? &tmWqkv : &tmW1;
          const int col = (t < 2 ? cg * 240 + t * 120 : cg * 216 + (t - 2) * 104) + (int)rank * 64;
          tma_2d_mc(sB + st * 8192 + rank * 4096, m, col, ks * 32, barF + 8 * st, (uint16_t)3);
          if (it < 16 && (it & 1)) {
            const int ka = (it >> 1) + 2;
            mbar_expect_tx(barA + 8 * ka, 16384);
            tma_2d(sA + ka * 16384, &tmX, ka * 64, rb * 128, barA + 8 * ka);
          }
        }
      }
    } else if (warp == 1) {
      const int r = cg * 16 + (lane >> 1), half = lane & 1;
      float acc = 0.f;
      mbar_wait(barA + 72, 0);
#pragma unroll 1
      for (int kb = half * 5; kb < half * 5 + 5; kb++) {
        mbar_wait(barA + 8 * kb, 0);
#pragma unroll
        for (int c = 0; c < 8; c++) {
          uint4 xv;
          asm volatile("ld.shared.v4.u32 {%0,%1,%2,%3}, [%4];" : "=r"(xv.x), "=r"(xv.y), "=r"(xv.z), "=r"(xv.w)
                       : "r"(sA + kb * 16384 + r * 128 + ((c ^ (r & 7)) << 4)));
          const uint4 wv = __ldg(reinterpret_cast<const uint4*>(gate_w + kb * 64 + c * 8));
          acc = fmaf(bf_lo(xv.x), bf_lo(wv.x), acc); acc = fmaf(bf_hi(xv.x), bf_hi(wv.x), acc);
          acc = fmaf(bf_lo(xv.y), bf_lo(wv.y), acc); acc = fmaf(bf_hi(xv.y), bf_hi(wv.y), acc);
          acc = fmaf(bf_lo(xv.z), bf_lo(wv.z), acc); acc = fmaf(bf_hi(xv.z), bf_hi(wv.z), acc);
          acc = fmaf(bf_lo(xv.w), bf_lo(wv.w), acc); acc = fmaf(bf_hi(xv.w), bf_hi(wv.w), acc);
        }
      }
      acc += __shfl_xor_sync(0xffffffffu, acc, 1);
      if (!half) g_gate[rb * 128 + r] = 1.f / (1.f + __expf(-acc));
    }
  } else {
    const int wgi = (warp >> 2) - 1, wq = warp & 3, g = lane >> 2, t4 = lane & 3;
    const uint32_t barE_self = mapa(barE, rank), barE_peer = mapa(barE, rank ^ 1);
    const bool elect = lane == 0;
    {
      float acc0[60], acc1[60];
      k1_mainloop<120>(acc0, acc1, [](float (&d)[60], uint64_t a, uint64_t b, int sd) { wgmma_ssp_n120_t01(d, a, b, sd); },
                       sA, sB, barA, barF, barE_self, barE_peer, wgi * 20, true, elect, wgi ? 1 : 0, wgi ? 2 : 1);
      if (warp == 4) STAMP(1);
      float nrm[6] = {0.f, 0.f, 0.f, 0.f, 0.f, 0.f};
      const int slot0 = cg * 12 + wgi * 6;
      k1_qkv_epi(acc0, nrm, slot0, rb * 16 + wq * 2, g, t4);
      k1_qkv_epi(acc1, nrm, slot0, rb * 16 + 8 + wq * 2, g, t4);
#pragma unroll
      for (int h = 0; h < 6; h++) {
        const uint32_t m = __reduce_max_sync(0xffffffffu, __float_as_uint(nrm[h]));
        if (lane == h) g_norm[(slot0 + h) * 64 + rb * 4 + wq] = __uint_as_float(m);
      }
    }
    if (warp == 4) STAMP(2);
    {
      float acc0[56], acc1[56];
      k1_mainloop<112>(acc0, acc1, [](float (&d)[56], uint64_t a, uint64_t b, int sd) { wgmma_ssp_n112_t01(d, a, b, sd); },
                       sA, sB, barA, barF, barE_self, barE_peer, 40 + wgi * 20, false, elect, wgi ? 1 : 2, wgi ? 0 : 1);
      if (warp == 8) STAMP(3);
      uint8_t* base = g_A2 + ((size_t)(rb * 296 + cg * 27 + wgi * 13) * 16 + wq * 2) * 128 + g * 16 + t4 * 4;
      const uint32_t* bp = reinterpret_cast<const uint32_t*>(b1 + cg * 216 + wgi * 104 + t4 * 2);
#pragma unroll
      for (int j = 0; j < 14; j++) {
        const uint32_t bv = __ldg(bp + j * 4);
        const float c0 = bf_lo(bv), c1 = bf_hi(bv);
        float h0 = fmaxf(acc0[4 * j] + c0, 0.f), h1 = fmaxf(acc0[4 * j + 1] + c1, 0.f);
        float h2 = fmaxf(acc0[4 * j + 2] + c0, 0.f), h3 = fmaxf(acc0[4 * j + 3] + c1, 0.f);
        st32(base + j * 2048, pack_bf16(h0 * h0, h1 * h1));
        st32(base + j * 2048 + 128, pack_bf16(h2 * h2, h3 * h3));
        h0 = fmaxf(acc1[4 * j] + c0, 0.f); h1 = fmaxf(acc1[4 * j + 1] + c1, 0.f);
        h2 = fmaxf(acc1[4 * j + 2] + c0, 0.f); h3 = fmaxf(acc1[4 * j + 3] + c1, 0.f);
        st32(base + j * 2048 + 1024, pack_bf16(h0 * h0, h1 * h1));
        st32(base + j * 2048 + 1024 + 128, pack_bf16(h2 * h2, h3 * h3));
      }
    }
    if (warp == 8) STAMP(4);
  }
  __syncwarp();
  cluster_arrive_relaxed();
  cluster_wait();
}

constexpr int KV_HEAD_BYTES = 256 * 768, Q_BYTES = 8 * 4096;
constexpr int AT_NCHUNK = 16, AT_CHUNK_BYTES = KV_HEAD_BYTES / AT_NCHUNK;
constexpr int AT_SMEM = KV_HEAD_BYTES + Q_BYTES + 1024 + 1024;

template <int T0, int T1, int TOFF>
__device__ __forceinline__ void exp_tiles(const float (&s)[32], uint32_t (&p)[16], uint32_t cmask, uint32_t cone) {
#pragma unroll
  for (int t = T0; t < T1; t++) {
#pragma unroll
    for (int h = 0; h < 2; h++) {
      const float x0 = s[4 * t + 2 * h], x1 = s[4 * t + 2 * h + 1];
      uint32_t r;
      if ((MUFU_MASK >> ((t + TOFF) & 15)) & 1) {
        r = pack_bf16(ex2(x0), ex2(x1));
      } else {
        const uint32_t u = __byte_perm(__float_as_uint(x0), __float_as_uint(x1), 0x5410);
        uint32_t g;
        asm("lop3.b32 %0, %1, %2, %3, 0xEA;" : "=r"(g) : "r"(u), "r"(cmask), "r"(cone));
        r = hfma2_bf16(g, g, 0x40034003u) + u - g;
      }
      p[2 * t + h] = r;
      asm volatile("" : "+r"(p[2 * t + h])::"memory");
    }
  }
}
template <int TOFF>
__device__ __forceinline__ void exp_pv(const float (&s)[32], uint32_t (&p)[16], float (&o)[12], uint64_t dv, int sd, uint32_t cmask, uint32_t cone) {
  exp_tiles<0, 4, TOFF>(s, p, cmask, cone);
  wg_fence();
  wgmma_rs_n24_t1(o, p[0], p[1], p[2], p[3], dv, sd);
  wgmma_rs_n24_t1(o, p[4], p[5], p[6], p[7], dv + 96, 1);
  exp_tiles<4, 8, TOFF>(s, p, cmask, cone);
  wg_fence();
  wgmma_rs_n24_t1(o, p[8], p[9], p[10], p[11], dv + 192, 1);
  wgmma_rs_n24_t1(o, p[12], p[13], p[14], p[15], dv + 288, 1);
}
__device__ __forceinline__ void qk64(float (&s)[32], uint64_t dq, uint64_t dk) {
  wgmma_ss0_n64_t00(s, dq, dk);
  wgmma_ss_n64_t00(s, dq + 16, dk + 16);
}
__device__ __forceinline__ void attn_store(const float (&o)[12], int row0, int head, int lane) {
  const int t4 = lane & 3;
  const float l0 = __shfl_sync(0xffffffffu, o[8], (lane & ~3) | 2), l1 = __shfl_sync(0xffffffffu, o[10], (lane & ~3) | 2);
  const float r0 = __fdividef(g_gate[row0], l0), r1 = __fdividef(g_gate[row0 + 8], l1);
  uint8_t* base = g_A2 + ((size_t)((row0 >> 7) * 296 + 216) * 16 + ((row0 & 127) >> 3)) * 128 + (row0 & 7) * 16;
#pragma unroll
  for (int tt = 0; tt < 3; tt++) {
    const int d = tt * 8 + 2 * t4;
    if (d < 20) {
      const int col = head * 20 + d;
      uint8_t* ptr = base + (col >> 3) * 2048 + (col & 7) * 2;
      *reinterpret_cast<uint32_t*>(ptr) = pack_bf16(o[4 * tt] * r0, o[4 * tt + 1] * r0);
      *reinterpret_cast<uint32_t*>(ptr + 128) = pack_bf16(o[4 * tt + 2] * r1, o[4 * tt + 3] * r1);
    }
  }
}

__device__ __forceinline__ void attn_slow(uint32_t sb, uint32_t bb, int wg, int rowbase, int head, int lane) {
  const uint64_t dk0 = mk_desc(sb, 128, 768, 0), dv0 = mk_desc(sb + 384, 768, 128, 0);
  const uint64_t dq0 = mk_desc(sb + KV_HEAD_BYTES + wg * 8192, 128, 512, 0);
#pragma unroll 1
  for (int mt = 0; mt < 2; mt++) {
    float o[12], s[32];
    uint32_t p[16];
#pragma unroll
    for (int i = 0; i < 12; i++) o[i] = 0.f;
    float m0 = -INFINITY, m1 = -INFINITY;
#pragma unroll 1
    for (int b = 0; b < 32; b++) {
      if (mt == 0 && !(b & 1)) mbar_wait(bb + 8 * (b >> 1), 0);
      wg_fence();
      qk64(s, dq0 + (uint32_t)(mt * 256), dk0 + (uint32_t)(b * 384));
      wg_commit();
      wg_wait<0>();
      fence_regs(s);
      float n0 = m0, n1 = m1;
#pragma unroll
      for (int t = 0; t < 8; t++) { n0 = fmaxf(n0, fmaxf(s[4 * t], s[4 * t + 1])); n1 = fmaxf(n1, fmaxf(s[4 * t + 2], s[4 * t + 3])); }
      n0 = fmaxf(n0, __shfl_xor_sync(0xffffffffu, n0, 1)); n0 = fmaxf(n0, __shfl_xor_sync(0xffffffffu, n0, 2));
      n1 = fmaxf(n1, __shfl_xor_sync(0xffffffffu, n1, 1)); n1 = fmaxf(n1, __shfl_xor_sync(0xffffffffu, n1, 2));
      const float a0 = ex2(m0 - n0), a1 = ex2(m1 - n1);
      m0 = n0; m1 = n1;
#pragma unroll
      for (int t = 0; t < 3; t++) { o[4 * t] *= a0; o[4 * t + 1] *= a0; o[4 * t + 2] *= a1; o[4 * t + 3] *= a1; }
#pragma unroll
      for (int t = 0; t < 8; t++) {
        p[2 * t] = pack_bf16(ex2(s[4 * t] - m0), ex2(s[4 * t + 1] - m0));
        p[2 * t + 1] = pack_bf16(ex2(s[4 * t + 2] - m1), ex2(s[4 * t + 3] - m1));
      }
      fence_regs(o);
      wg_fence();
#pragma unroll
      for (int k = 0; k < 4; k++) wgmma_rs_n24_t1(o, p[4 * k], p[4 * k + 1], p[4 * k + 2], p[4 * k + 3], dv0 + (uint32_t)(b * 384 + k * 96), 1);
      wg_commit();
      wg_wait<0>();
      fence_regs(o);
    }
    attn_store(o, rowbase + mt * 64, head, lane);
  }
}

__global__ void __launch_bounds__(512, 1) k2_attn(int opaque_zero) {
  extern __shared__ uint8_t smem_raw[];
  const uint32_t sb = (smem_u32(smem_raw) + 1023u) & ~1023u;
  const uint32_t bb = sb + KV_HEAD_BYTES + Q_BYTES;
  const int tid = threadIdx.x, lane = tid & 31;
  const int warp = __shfl_sync(0xffffffffu, tid >> 5, 0), wg = warp >> 2;
  const int head = blockIdx.x >> 2, qb = blockIdx.x & 3;
  if (tid == 0) {
    STAMP(5);
    for (int i = 0; i <= AT_NCHUNK; i++) mbar_init(bb + 8 * i, 1);
    fence_barrier_init();
    fence_proxy_async();
  }
  pdl_launch();
  pdl_wait();
  if (tid == 0) {
    STAMP(6);
    mbar_expect_tx(bb + 8 * AT_NCHUNK, Q_BYTES);
    bulk_g2s(sb + KV_HEAD_BYTES, g_QKV + (size_t)blockIdx.x * Q_BYTES, Q_BYTES, bb + 8 * AT_NCHUNK);
    for (int i = 0; i < AT_NCHUNK; i++) {
      mbar_expect_tx(bb + 8 * i, AT_CHUNK_BYTES);
      bulk_g2s(sb + i * AT_CHUNK_BYTES, g_QKV + KV_OFF + (size_t)head * KV_HEAD_BYTES + i * AT_CHUNK_BYTES, AT_CHUNK_BYTES, bb + 8 * i);
    }
  }
  bool fast;
  {
    const uint32_t* nb = reinterpret_cast<const uint32_t*>(g_norm);
    const uint2 k2 = *reinterpret_cast<const uint2*>(nb + (32 + head) * 64 + lane * 2);
    const uint2 v2 = *reinterpret_cast<const uint2*>(nb + (64 + head) * 64 + lane * 2);
    const float nq = __uint_as_float(__reduce_max_sync(0xffffffffu, nb[head * 64 + qb * 16 + (lane & 15)]));
    const float nk = __uint_as_float(__reduce_max_sync(0xffffffffu, max(k2.x, k2.y)));
    const float nv = __uint_as_float(__reduce_max_sync(0xffffffffu, max(v2.x, v2.y)));
    fast = (nq * nk <= 2304.0f) && (nq <= 1e30f) && (nk <= 1e30f) && (nv <= 1e30f) && (nv >= 1e-18f);
  }
  const int rowbase = qb * 512 + wg * 128 + (warp & 3) * 16 + (lane >> 2);
  __syncthreads();
  mbar_wait(bb + 8 * AT_NCHUNK, 0);
  if (!fast) {
    *reinterpret_cast<uint2*>(smem_raw + (sb - smem_u32(smem_raw)) + KV_HEAD_BYTES + (tid >> 3) * 512 + 256 + (tid & 7) * 16 + 8) = make_uint2(0u, 0u);
    fence_proxy_async();
    __syncthreads();
    attn_slow(sb, bb, wg, rowbase, head, lane);
    return;
  }
  uint32_t cmask = 0x007F007Fu + opaque_zero, cone = 0x3F803F80u + opaque_zero;
  const uint64_t dk0 = mk_desc(sb, 128, 768, 0), dv0 = mk_desc(sb + 384, 768, 128, 0);
  const uint64_t dq0 = mk_desc(sb + KV_HEAD_BYTES + wg * 8192, 128, 512, 0);
  float o[12], s0[32], s1[32];
  uint32_t p0[16], p1[16];
#pragma unroll
  for (int i = 0; i < 12; i++) o[i] = 0.f;
  fence_regs(o);
  mbar_wait(bb, 0);
  wg_fence();
  qk64(s0, dq0, dk0);
  wg_commit();
  wg_wait<0>();
  fence_regs(s0);
#pragma unroll 1
  for (int it = 0; it < 32; it++) {
    const int c = it & 15, mt = it >> 4;
    const uint64_t dq = dq0 + (uint32_t)(mt * 256);
    const uint32_t off = c * 768;
    wg_fence();
    qk64(s1, dq, dk0 + (off + 384));
    wg_commit();
    exp_pv<0>(s0, p0, o, dv0 + off, c, cmask, cone);
    wg_commit();
    wg_wait<1>();
    fence_regs(s1);
    const int cn = (c + 1) & 15;
    const uint64_t dqn = dq0 + (uint32_t)((((it + 1) >> 4) & 1) * 256);
    if (it < 15) mbar_wait(bb + 8 * cn, 0);
    wg_fence();
    qk64(s0, dqn, dk0 + (uint32_t)(cn * 768));
    wg_commit();
    exp_pv<8>(s1, p1, o, dv0 + (off + 384), 1, cmask, cone);
    wg_commit();
    wg_wait<0>();
    fence_regs(s0);
    fence_regs(o);
    if (c == 15) attn_store(o, rowbase + mt * 64, head, lane);
  }
  if (warp == 0) STAMP(8);
}

constexpr int K3_NST = 8, K3_STAGE = 8192 + 10240;
constexpr int K3_RED = 128 * 80 * 4;
constexpr int K3_SMEM = K3_NST * K3_STAGE + K3_RED + 1024 + 1024;

__global__ void __cluster_dims__(2, 1, 1) __launch_bounds__(288, 1)
k3_out(const __grid_constant__ CUtensorMap tmW2, const __grid_constant__ CUtensorMap tmWo, const __nv_bfloat16* __restrict__ b2,
       __nv_bfloat16* __restrict__ out) {
  extern __shared__ uint8_t smem_raw[];
  const uint32_t sb = (smem_u32(smem_raw) + 1023u) & ~1023u;
  const uint32_t sRed = sb + K3_NST * K3_STAGE, barF = sRed + K3_RED, barE = barF + 8 * K3_NST, barR = barE + 8 * K3_NST;
  const int tid = threadIdx.x, lane = tid & 31;
  const int warp = __shfl_sync(0xffffffffu, tid >> 5, 0);
  const uint32_t rank = cluster_rank();
  const int tile = blockIdx.x >> 1, rb = tile >> 2, ct = tile & 3;
  if (tid == 0) {
    STAMP(9);
    prefetch_tmap(&tmW2); prefetch_tmap(&tmWo);
    for (int i = 0; i < K3_NST; i++) { mbar_init(barF + 8 * i, 1); mbar_init(barE + 8 * i, 8); }
    mbar_init(barR, 1);
    fence_barrier_init();
    mbar_expect_tx(barR, K3_RED);
  }
  __syncwarp();
  cluster_arrive();
  cluster_wait();
  if (warp == 8) {
    if (lane == 0) {
      const int s0 = rank * 37;
      const uint8_t* asrc = g_A2 + (size_t)rb * 296 * 2048;
      for (int i = 0; i < K3_NST; i++) {
        const int s = s0 + i;
        mbar_expect_tx(barF + 8 * i, K3_STAGE);
        for (int b = 0; b < 5; b++) tma_2d(sb + i * K3_STAGE + 8192 + b * 2048, &tmW2, ct * 160 + b * 32, s * 32, barF + 8 * i);
      }
      pdl_wait();
      for (int i = 0; i < K3_NST; i++) bulk_g2s(sb + i * K3_STAGE, asrc + (size_t)(s0 + i) * 8192, 8192, barF + 8 * i);
#pragma unroll 1
      for (int i = K3_NST; i < 37; i++) {
        const int st = i & (K3_NST - 1), s = s0 + i;
        mbar_wait(barE + 8 * st, ((i / K3_NST) - 1) & 1);
        mbar_expect_tx(barF + 8 * st, K3_STAGE);
        bulk_g2s(sb + st * K3_STAGE, asrc + (size_t)s * 8192, 8192, barF + 8 * st);
        const CUtensorMap* m = s < 54 ? &tmW2 : &tmWo;
        const int k = (s < 54 ? s : s - 54) * 32;
        for (int b = 0; b < 5; b++) tma_2d(sb + st * K3_STAGE + 8192 + b * 2048, m, ct * 160 + b * 32, k, barF + 8 * st);
      }
    }
  } else {
    const int wgi = warp >> 2, wq = warp & 3, g = lane >> 2, t4 = lane & 3;
    const int rloc = wgi * 64 + wq * 16 + g, row = rb * 128 + rloc;
    const int col0 = ct * 160 + rank * 80 + t4 * 2;
    uint32_t bias[10];
#pragma unroll
    for (int j = 0; j < 10; j++) bias[j] = __ldg(reinterpret_cast<const uint32_t*>(b2 + col0 + j * 8));
    pdl_wait();
    if (warp == 0) STAMP(10);
    const float w0 = 1.f - g_gate[row], w1 = 1.f - g_gate[row + 8];
    float acc[80];
    const uint64_t dA0 = mk_desc(sb + wgi * 1024, 2048, 128, 0), dB0 = mk_desc(sb + 8192, 2048, 512, 2);
    const int nsw = rank ? 17 : 37;
    fence_regs(acc);
#pragma unroll 1
    for (int i = 0; i < 37; i++) {
      const int st = i & (K3_NST - 1);
      mbar_wait(barF + 8 * st, (i / K3_NST) & 1);
      const uint32_t off = st * (K3_STAGE >> 4);
      wg_fence();
      wgmma_ssp_n160_t01(acc, dA0 + off, dB0 + off, i);
      wgmma_ssp_n160_t01(acc, dA0 + off + 256, dB0 + off + 64, 1);
      wg_commit();
      if (i + 1 == nsw) {
        wg_wait<0>();
        fence_regs(acc);
#pragma unroll
        for (int j = 0; j < 20; j++) { acc[4 * j] *= w0; acc[4 * j + 1] *= w0; acc[4 * j + 2] *= w1; acc[4 * j + 3] *= w1; }
        fence_regs(acc);
      } else {
        wg_wait<1>();
      }
      if (i > 0 && lane == 0) mbar_arrive(barE + 8 * ((i - 1) & (K3_NST - 1)));
    }
    wg_wait<0>();
    fence_regs(acc);
    if (warp == 0) STAMP(11);
    const uint32_t peerRed = mapa(sRed, rank ^ 1) + tid * 16, peerBar = mapa(barR, rank ^ 1);
#pragma unroll
    for (int j = 0; j < 10; j++) {
      const float a0 = rank ? acc[4 * j] : acc[40 + 4 * j], a1 = rank ? acc[4 * j + 1] : acc[40 + 4 * j + 1];
      const float a2 = rank ? acc[4 * j + 2] : acc[40 + 4 * j + 2], a3 = rank ? acc[4 * j + 3] : acc[40 + 4 * j + 3];
      asm volatile("st.async.weak.shared::cluster.mbarrier::complete_tx::bytes.v4.f32 [%0], {%1, %2, %3, %4}, [%5];"
                   ::"r"(peerRed + j * 4096), "f"(a0), "f"(a1), "f"(a2), "f"(a3), "r"(peerBar) : "memory");
    }
    mbar_wait(barR, 0);
    if (warp == 0) STAMP(13);
#pragma unroll
    for (int j = 0; j < 10; j++) {
      float p0, p1, p2, p3;
      asm volatile("ld.shared.v4.f32 {%0, %1, %2, %3}, [%4];" : "=f"(p0), "=f"(p1), "=f"(p2), "=f"(p3) : "r"(sRed + tid * 16 + j * 4096));
      const float a0 = rank ? acc[40 + 4 * j] : acc[4 * j], a1 = rank ? acc[40 + 4 * j + 1] : acc[4 * j + 1];
      const float a2 = rank ? acc[40 + 4 * j + 2] : acc[4 * j + 2], a3 = rank ? acc[40 + 4 * j + 3] : acc[4 * j + 3];
      const float c0 = bf_lo(bias[j]), c1 = bf_hi(bias[j]);
      *reinterpret_cast<uint32_t*>(out + (size_t)row * D_ + col0 + j * 8) = pack_bf16(fmaf(w0, c0, a0 + p0), fmaf(w0, c1, a1 + p1));
      *reinterpret_cast<uint32_t*>(out + (size_t)(row + 8) * D_ + col0 + j * 8) = pack_bf16(fmaf(w1, c0, a2 + p2), fmaf(w1, c1, a3 + p3));
    }
    if (warp == 0) STAMP(12);
  }
}

typedef CUresult (*EncodeFn)(CUtensorMap*, CUtensorMapDataType, cuuint32_t, void*, const cuuint64_t*, const cuuint64_t*, const cuuint32_t*,
                             const cuuint32_t*, CUtensorMapInterleave, CUtensorMapSwizzle, CUtensorMapL2promotion, CUtensorMapFloatOOBfill);

void make_map(EncodeFn fn, CUtensorMap* m, const void* ptr, uint64_t inner, uint64_t outer, uint32_t box_inner, uint32_t box_outer, CUtensorMapSwizzle sw) {
  cuuint64_t dims[2] = {inner, outer};
  cuuint64_t strides[1] = {inner * 2};
  cuuint32_t box[2] = {box_inner, box_outer};
  cuuint32_t es[2] = {1, 1};
  fn(m, CU_TENSOR_MAP_DATA_TYPE_BFLOAT16, 2, const_cast<void*>(ptr), dims, strides, box, es, CU_TENSOR_MAP_INTERLEAVE_NONE, sw,
     CU_TENSOR_MAP_L2_PROMOTION_L2_256B, CU_TENSOR_MAP_FLOAT_OOB_FILL_NONE);
}

}

extern "C" void kernel_launch(void* const* d_in, const int* in_sizes, int n_in, void* d_out, int out_size) {
  (void)in_sizes; (void)n_in; (void)out_size;
  const __nv_bfloat16* x = (const __nv_bfloat16*)d_in[0];
  const __nv_bfloat16* wqkv = (const __nv_bfloat16*)d_in[1];
  const __nv_bfloat16* wo = (const __nv_bfloat16*)d_in[2];
  const __nv_bfloat16* w1 = (const __nv_bfloat16*)d_in[4];
  const __nv_bfloat16* b1 = (const __nv_bfloat16*)d_in[5];
  const __nv_bfloat16* w2 = (const __nv_bfloat16*)d_in[6];
  const __nv_bfloat16* b2 = (const __nv_bfloat16*)d_in[7];
  const __nv_bfloat16* gw = (const __nv_bfloat16*)d_in[8];

  static EncodeFn enc = nullptr;
  if (!enc) {
    void* p = nullptr;
    cudaDriverEntryPointQueryResult qr;
    cudaGetDriverEntryPoint("cuTensorMapEncodeTiled", &p, cudaEnableDefault, &qr);
    enc = (EncodeFn)p;
    cudaFuncSetAttribute(k1_proj, cudaFuncAttributeMaxDynamicSharedMemorySize, K1_SMEM);
    cudaFuncSetAttribute(k2_attn, cudaFuncAttributeMaxDynamicSharedMemorySize, AT_SMEM);
    cudaFuncSetAttribute(k3_out, cudaFuncAttributeMaxDynamicSharedMemorySize, K3_SMEM);
  }
  CUtensorMap tmX, tmWqkv, tmW1, tmW2, tmWo;
  make_map(enc, &tmX, x, D_, S_, 64, 128, CU_TENSOR_MAP_SWIZZLE_128B);
  make_map(enc, &tmWqkv, wqkv, 3 * D_, D_, 64, 32, CU_TENSOR_MAP_SWIZZLE_128B);
  make_map(enc, &tmW1, w1, F_, D_, 64, 32, CU_TENSOR_MAP_SWIZZLE_128B);
  make_map(enc, &tmW2, w2, D_, F_, 32, 32, CU_TENSOR_MAP_SWIZZLE_64B);
  make_map(enc, &tmWo, wo, D_, D_, 32, 32, CU_TENSOR_MAP_SWIZZLE_64B);

  cudaStream_t st = cudaStreamPerThread;
  k1_proj<<<128, 384, K1_SMEM, st>>>(tmX, tmWqkv, tmW1, b1, gw);

  cudaLaunchAttribute at[1];
  at[0].id = cudaLaunchAttributeProgrammaticStreamSerialization;
  at[0].val.programmaticStreamSerializationAllowed = 1;
  {
    cudaLaunchConfig_t cfg = {};
    cfg.gridDim = dim3(128); cfg.blockDim = dim3(512); cfg.dynamicSmemBytes = AT_SMEM; cfg.stream = st;
    cfg.attrs = at; cfg.numAttrs = 1;
    cudaLaunchKernelEx(&cfg, k2_attn, 0);
  }
  {
    cudaLaunchConfig_t cfg = {};
    cfg.gridDim = dim3(128); cfg.blockDim = dim3(288); cfg.dynamicSmemBytes = K3_SMEM; cfg.stream = st;
    cfg.attrs = at; cfg.numAttrs = 1;
    cudaLaunchKernelEx(&cfg, k3_out, tmW2, tmWo, b2, (__nv_bfloat16*)d_out);
  }
}
```

```cpp
#include <cuda_runtime.h>
#include <cuda_bf16.h>
#include <cuda.h>
#include <stdint.h>

namespace {

constexpr int S_ = 2048, D_ = 640, NH = 32, F_ = 1728;

constexpr uint32_t KV_OFF = NH * 256 * 512;
__device__ __align__(1024) uint8_t g_QKV[NH * 256 * 512 + NH * 256 * 768];
__device__ __align__(1024) uint8_t g_A2[16 * 296 * 2048];
__device__ float g_gate[S_];
__device__ __align__(16) float g_norm[96 * 128];

constexpr uint32_t MUFU_MASK = 0x5151u;

#define STAMP(i) do { } while (0)

__device__ __forceinline__ uint32_t smem_u32(const void* p) { return (uint32_t)__cvta_generic_to_shared(p); }
__device__ __forceinline__ void wg_fence() { asm volatile("wgmma.fence.sync.aligned;" ::: "memory"); }
__device__ __forceinline__ void wg_commit() { asm volatile("wgmma.commit_group.sync.aligned;" ::: "memory"); }
template <int N> __device__ __forceinline__ void wg_wait() { asm volatile("wgmma.wait_group.sync.aligned %0;" ::"n"(N) : "memory"); }
template <int N> __device__ __forceinline__ void fence_regs(float (&r)[N]) {
#pragma unroll
  for (int i = 0; i < N; i++) asm volatile("" : "+f"(r[i])::"memory");
}
__device__ __forceinline__ float ex2(float x) { float y; asm("ex2.approx.ftz.f32 %0, %1;" : "=f"(y) : "f"(x)); return y; }
__device__ __forceinline__ uint32_t pack_bf16(float lo, float hi) { uint32_t y; asm("cvt.rn.bf16x2.f32 %0, %1, %2;" : "=r"(y) : "f"(hi), "f"(lo)); return y; }
__device__ __forceinline__ uint32_t hfma2_bf16(uint32_t a, uint32_t b, uint32_t c) { uint32_t y; asm("fma.rn.bf16x2 %0, %1, %2, %3;" : "=r"(y) : "r"(a), "r"(b), "r"(c)); return y; }
__device__ __forceinline__ float bf_lo(uint32_t v) { return __uint_as_float(v << 16); }
__device__ __forceinline__ float bf_hi(uint32_t v) { return __uint_as_float(v & 0xffff0000u); }
__device__ __forceinline__ void mbar_init(uint32_t bar, int cnt) { asm volatile("mbarrier.init.shared::cta.b64 [%0], %1;" ::"r"(bar), "r"(cnt)); }
__device__ __forceinline__ void mbar_expect_tx(uint32_t bar, uint32_t bytes) { asm volatile("mbarrier.arrive.expect_tx.shared::cta.b64 _, [%0], %1;" ::"r"(bar), "r"(bytes) : "memory"); }
__device__ __forceinline__ void mbar_arrive(uint32_t bar) { asm volatile("mbarrier.arrive.shared::cta.b64 _, [%0];" ::"r"(bar) : "memory"); }
__device__ __forceinline__ void mbar_arrive_cluster(uint32_t cluster_addr) { asm volatile("mbarrier.arrive.shared::cluster.b64 _, [%0];" ::"r"(cluster_addr) : "memory"); }
__device__ __forceinline__ void mbar_wait(uint32_t bar, uint32_t parity) {
  asm volatile(
      "{\n.reg .pred p;\n.reg .u32 n;\n"
      "mbarrier.try_wait.parity.shared::cta.b64 p, [%0], %1;\n"
      "@p bra DONE;\n"
      "mov.u32 n, 0;\n"
      "LOOP:\n"
      "mbarrier.try_wait.parity.shared::cta.b64 p, [%0], %1;\n"
      "@p bra DONE;\n"
      "add.u32 n, n, 1;\n"
      "setp.lt.u32 p, n, 0x1000000;\n"
      "@p bra LOOP;\n"
      "trap;\n"
      "DONE:\n}\n" ::"r"(bar), "r"(parity) : "memory");
}
__device__ __forceinline__ void bulk_g2s(uint32_t dst, const void* src, uint32_t bytes, uint32_t bar) {
  asm volatile("cp.async.bulk.shared::cluster.global.mbarrier::complete_tx::bytes [%0], [%1], %2, [%3];" ::"r"(dst), "l"(src), "r"(bytes), "r"(bar) : "memory");
}
__device__ __forceinline__ void tma_2d(uint32_t dst, const CUtensorMap* m, int c0, int c1, uint32_t bar) {
  asm volatile("cp.async.bulk.tensor.2d.shared::cluster.global.mbarrier::complete_tx::bytes [%0], [%1, {%3, %4}], [%2];" ::"r"(dst), "l"(m), "r"(bar), "r"(c0), "r"(c1) : "memory");
}
__device__ __forceinline__ void tma_2d_mc(uint32_t dst, const CUtensorMap* m, int c0, int c1, uint32_t bar, uint16_t mask) {
  asm volatile("cp.async.bulk.tensor.2d.shared::cluster.global.mbarrier::complete_tx::bytes.multicast::cluster [%0], [%1, {%3, %4}], [%2], %5;" ::"r"(dst), "l"(m), "r"(bar), "r"(c0), "r"(c1), "h"(mask) : "memory");
}
__device__ __forceinline__ uint32_t mapa(uint32_t addr, uint32_t rank) { uint32_t r; asm("mapa.shared::cluster.u32 %0, %1, %2;" : "=r"(r) : "r"(addr), "r"(rank)); return r; }
__device__ __forceinline__ uint32_t cluster_rank() { uint32_t r; asm("mov.u32 %0, %%cluster_ctarank;" : "=r"(r)); return r; }
__device__ __forceinline__ void cluster_arrive() { asm volatile("barrier.cluster.arrive.release.aligned;" ::: "memory"); }
__device__ __forceinline__ void cluster_arrive_relaxed() { asm volatile("barrier.cluster.arrive.relaxed.aligned;" ::: "memory"); }
__device__ __forceinline__ void cluster_wait() { asm volatile("barrier.cluster.wait.acquire.aligned;" ::: "memory"); }
__device__ __forceinline__ void bar_sync(int id, int n) { asm volatile("bar.sync %0, %1;" ::"r"(id), "r"(n) : "memory"); }
__device__ __forceinline__ void bar_arrive(int id, int n) { asm volatile("bar.arrive %0, %1;" ::"r"(id), "r"(n) : "memory"); }
__device__ __forceinline__ void pdl_launch() { asm volatile("griddepcontrol.launch_dependents;" ::: "memory"); }
__device__ __forceinline__ void pdl_wait() { asm volatile("griddepcontrol.wait;" ::: "memory"); }
__device__ __forceinline__ void fence_barrier_init() { asm volatile("fence.mbarrier_init.release.cluster;" ::: "memory"); }
__device__ __forceinline__ void fence_proxy_async() { asm volatile("fence.proxy.async.shared::cta;" ::: "memory"); }
__device__ __forceinline__ void prefetch_tmap(const CUtensorMap* m) { asm volatile("prefetch.tensormap [%0];" ::"l"(m) : "memory"); }
__device__ __forceinline__ uint64_t mk_desc(uint32_t addr, uint32_t lbo, uint32_t sbo, uint32_t mode) {
  return (uint64_t)((addr & 0x3FFFF) >> 4) | ((uint64_t)(lbo >> 4) << 16) | ((uint64_t)(sbo >> 4) << 32) | ((uint64_t)mode << 62);
}

__device__ __forceinline__ void wgmma_ssp_n240_t01(float (&d)[120], uint64_t da, uint64_t db, int sd) {
  asm volatile("{\n.reg .pred p;\nsetp.ne.b32 p, %122, 0;\n"
    "wgmma.mma_async.sync.aligned.m64n240k16.f32.bf16.bf16 {%0, %1, %2, %3, %4, %5, %6, %7, %8, %9, %10, %11, %12, %13, %14, %15, %16, %17, %18, %19, %20, %21, %22, %23, %24, %25, %26, %27, %28, %29, %30, %31, %32, %33, %34, %35, %36, %37, %38, %39, %40, %41, %42, %43, %44, %45, %46, %47, %48, %49, %50, %51, %52, %53, %54, %55, %56, %57, %58, %59, %60, %61, %62, %63, %64, %65, %66, %67, %68, %69, %70, %71, %72, %73, %74, %75, %76, %77, %78, %79, %80, %81, %82, %83, %84, %85, %86, %87, %88, %89, %90, %91, %92, %93, %94, %95, %96, %97, %98, %99, %100, %101, %102, %103, %104, %105, %106, %107, %108, %109, %110, %111, %112, %113, %114, %115, %116, %117, %118, %119}, %120, %121, p, 1, 1, 0, 1;\n}\n"
    : "+f"(d[0]), "+f"(d[1]), "+f"(d[2]), "+f"(d[3]), "+f"(d[4]), "+f"(d[5]), "+f"(d[6]), "+f"(d[7]), "+f"(d[8]), "+f"(d[9]), "+f"(d[10]), "+f"(d[11]), "+f"(d[12]), "+f"(d[13]), "+f"(d[14]), "+f"(d[15]), "+f"(d[16]), "+f"(d[17]), "+f"(d[18]), "+f"(d[19]), "+f"(d[20]), "+f"(d[21]), "+f"(d[22]), "+f"(d[23]), "+f"(d[24]), "+f"(d[25]), "+f"(d[26]), "+f"(d[27]), "+f"(d[28]), "+f"(d[29]), "+f"(d[30]), "+f"(d[31]), "+f"(d[32]), "+f"(d[33]), "+f"(d[34]), "+f"(d[35]), "+f"(d[36]), "+f"(d[37]), "+f"(d[38]), "+f"(d[39]), "+f"(d[40]), "+f"(d[41]), "+f"(d[42]), "+f"(d[43]), "+f"(d[44]), "+f"(d[45]), "+f"(d[46]), "+f"(d[47]), "+f"(d[48]), "+f"(d[49]), "+f"(d[50]), "+f"(d[51]), "+f"(d[52]), "+f"(d[53]), "+f"(d[54]), "+f"(d[55]), "+f"(d[56]), "+f"(d[57]), "+f"(d[58]), "+f"(d[59]), "+f"(d[60]), "+f"(d[61]), "+f"(d[62]), "+f"(d[63]), "+f"(d[64]), "+f"(d[65]), "+f"(d[66]), "+f"(d[67]), "+f"(d[68]), "+f"(d[69]), "+f"(d[70]), "+f"(d[71]), "+f"(d[72]), "+f"(d[73]), "+f"(d[74]), "+f"(d[75]), "+f"(d[76]), "+f"(d[77]), "+f"(d[78]), "+f"(d[79]), "+f"(d[80]), "+f"(d[81]), "+f"(d[82]), "+f"(d[83]), "+f"(d[84]), "+f"(d[85]), "+f"(d[86]), "+f"(d[87]), "+f"(d[88]), "+f"(d[89]), "+f"(d[90]), "+f"(d[91]), "+f"(d[92]), "+f"(d[93]), "+f"(d[94]), "+f"(d[95]), "+f"(d[96]), "+f"(d[97]), "+f"(d[98]), "+f"(d[99]), "+f"(d[100]), "+f"(d[101]), "+f"(d[102]), "+f"(d[103]), "+f"(d[104]), "+f"(d[105]), "+f"(d[106]), "+f"(d[107]), "+f"(d[108]), "+f"(d[109]), "+f"(d[110]), "+f"(d[111]), "+f"(d[112]), "+f"(d[113]), "+f"(d[114]), "+f"(d[115]), "+f"(d[116]), "+f"(d[117]), "+f"(d[118]), "+f"(d[119])
    : "l"(da), "l"(db), "r"(sd));
}
__device__ __forceinline__ void wgmma_ssp_n216_t01(float (&d)[108], uint64_t da, uint64_t db, int sd) {
  asm volatile("{\n.reg .pred p;\nsetp.ne.b32 p, %110, 0;\n"
    "wgmma.mma_async.sync.aligned.m64n216k16.f32.bf16.bf16 {%0, %1, %2, %3, %4, %5, %6, %7, %8, %9, %10, %11, %12, %13, %14, %15, %16, %17, %18, %19, %20, %21, %22, %23, %24, %25, %26, %27, %28, %29, %30, %31, %32, %33, %34, %35, %36, %37, %38, %39, %40, %41, %42, %43, %44, %45, %46, %47, %48, %49, %50, %51, %52, %53, %54, %55, %56, %57, %58, %59, %60, %61, %62, %63, %64, %65, %66, %67, %68, %69, %70, %71, %72, %73, %74, %75, %76, %77, %78, %79, %80, %81, %82, %83, %84, %85, %86, %87, %88, %89, %90, %91, %92, %93, %94, %95, %96, %97, %98, %99, %100, %101, %102, %103, %104, %105, %106, %107}, %108, %109, p, 1, 1, 0, 1;\n}\n"
    : "+f"(d[0]), "+f"(d[1]), "+f"(d[2]), "+f"(d[3]), "+f"(d[4]), "+f"(d[5]), "+f"(d[6]), "+f"(d[7]), "+f"(d[8]), "+f"(d[9]), "+f"(d[10]), "+f"(d[11]), "+f"(d[12]), "+f"(d[13]), "+f"(d[14]), "+f"(d[15]), "+f"(d[16]), "+f"(d[17]), "+f"(d[18]), "+f"(d[19]), "+f"(d[20]), "+f"(d[21]), "+f"(d[22]), "+f"(d[23]), "+f"(d[24]), "+f"(d[25]), "+f"(d[26]), "+f"(d[27]), "+f"(d[28]), "+f"(d[29]), "+f"(d[30]), "+f"(d[31]), "+f"(d[32]), "+f"(d[33]), "+f"(d[34]), "+f"(d[35]), "+f"(d[36]), "+f"(d[37]), "+f"(d[38]), "+f"(d[39]), "+f"(d[40]), "+f"(d[41]), "+f"(d[42]), "+f"(d[43]), "+f"(d[44]), "+f"(d[45]), "+f"(d[46]), "+f"(d[47]), "+f"(d[48]), "+f"(d[49]), "+f"(d[50]), "+f"(d[51]), "+f"(d[52]), "+f"(d[53]), "+f"(d[54]), "+f"(d[55]), "+f"(d[56]), "+f"(d[57]), "+f"(d[58]), "+f"(d[59]), "+f"(d[60]), "+f"(d[61]), "+f"(d[62]), "+f"(d[63]), "+f"(d[64]), "+f"(d[65]), "+f"(d[66]), "+f"(d[67]), "+f"(d[68]), "+f"(d[69]), "+f"(d[70]), "+f"(d[71]), "+f"(d[72]), "+f"(d[73]), "+f"(d[74]), "+f"(d[75]), "+f"(d[76]), "+f"(d[77]), "+f"(d[78]), "+f"(d[79]), "+f"(d[80]), "+f"(d[81]), "+f"(d[82]), "+f"(d[83]), "+f"(d[84]), "+f"(d[85]), "+f"(d[86]), "+f"(d[87]), "+f"(d[88]), "+f"(d[89]), "+f"(d[90]), "+f"(d[91]), "+f"(d[92]), "+f"(d[93]), "+f"(d[94]), "+f"(d[95]), "+f"(d[96]), "+f"(d[97]), "+f"(d[98]), "+f"(d[99]), "+f"(d[100]), "+f"(d[101]), "+f"(d[102]), "+f"(d[103]), "+f"(d[104]), "+f"(d[105]), "+f"(d[106]), "+f"(d[107])
    : "l"(da), "l"(db), "r"(sd));
}
__device__ __forceinline__ void wgmma_ssp_n160_t01(float (&d)[80], uint64_t da, uint64_t db, int sd) {
  asm volatile("{\n.reg .pred p;\nsetp.ne.b32 p, %82, 0;\n"
    "wgmma.mma_async.sync.aligned.m64n160k16.f32.bf16.bf16 {%0, %1, %2, %3, %4, %5, %6, %7, %8, %9, %10, %11, %12, %13, %14, %15, %16, %17, %18, %19, %20, %21, %22, %23, %24, %25, %26, %27, %28, %29, %30, %31, %32, %33, %34, %35, %36, %37, %38, %39, %40, %41, %42, %43, %44, %45, %46, %47, %48, %49, %50, %51, %52, %53, %54, %55, %56, %57, %58, %59, %60, %61, %62, %63, %64, %65, %66, %67, %68, %69, %70, %71, %72, %73, %74, %75, %76, %77, %78, %79}, %80, %81, p, 1, 1, 0, 1;\n}\n"
    : "+f"(d[0]), "+f"(d[1]), "+f"(d[2]), "+f"(d[3]), "+f"(d[4]), "+f"(d[5]), "+f"(d[6]), "+f"(d[7]), "+f"(d[8]), "+f"(d[9]), "+f"(d[10]), "+f"(d[11]), "+f"(d[12]), "+f"(d[13]), "+f"(d[14]), "+f"(d[15]), "+f"(d[16]), "+f"(d[17]), "+f"(d[18]), "+f"(d[19]), "+f"(d[20]), "+f"(d[21]), "+f"(d[22]), "+f"(d[23]), "+f"(d[24]), "+f"(d[25]), "+f"(d[26]), "+f"(d[27]), "+f"(d[28]), "+f"(d[29]), "+f"(d[30]), "+f"(d[31]), "+f"(d[32]), "+f"(d[33]), "+f"(d[34]), "+f"(d[35]), "+f"(d[36]), "+f"(d[37]), "+f"(d[38]), "+f"(d[39]), "+f"(d[40]), "+f"(d[41]), "+f"(d[42]), "+f"(d[43]), "+f"(d[44]), "+f"(d[45]), "+f"(d[46]), "+f"(d[47]), "+f"(d[48]), "+f"(d[49]), "+f"(d[50]), "+f"(d[51]), "+f"(d[52]), "+f"(d[53]), "+f"(d[54]), "+f"(d[55]), "+f"(d[56]), "+f"(d[57]), "+f"(d[58]), "+f"(d[59]), "+f"(d[60]), "+f"(d[61]), "+f"(d[62]), "+f"(d[63]), "+f"(d[64]), "+f"(d[65]), "+f"(d[66]), "+f"(d[67]), "+f"(d[68]), "+f"(d[69]), "+f"(d[70]), "+f"(d[71]), "+f"(d[72]), "+f"(d[73]), "+f"(d[74]), "+f"(d[75]), "+f"(d[76]), "+f"(d[77]), "+f"(d[78]), "+f"(d[79])
    : "l"(da), "l"(db), "r"(sd));
}
__device__ __forceinline__ void wgmma_ss_n64_t00(float (&d)[32], uint64_t da, uint64_t db) {
  asm volatile("{\n.reg .pred p;\nsetp.ne.b32 p, 1, 0;\n"
    "wgmma.mma_async.sync.aligned.m64n64k16.f32.bf16.bf16 {%0, %1, %2, %3, %4, %5, %6, %7, %8, %9, %10, %11, %12, %13, %14, %15, %16, %17, %18, %19, %20, %21, %22, %23, %24, %25, %26, %27, %28, %29, %30, %31}, %32, %33, p, 1, 1, 0, 0;\n}\n"
    : "+f"(d[0]), "+f"(d[1]), "+f"(d[2]), "+f"(d[3]), "+f"(d[4]), "+f"(d[5]), "+f"(d[6]), "+f"(d[7]), "+f"(d[8]), "+f"(d[9]), "+f"(d[10]), "+f"(d[11]), "+f"(d[12]), "+f"(d[13]), "+f"(d[14]), "+f"(d[15]), "+f"(d[16]), "+f"(d[17]), "+f"(d[18]), "+f"(d[19]), "+f"(d[20]), "+f"(d[21]), "+f"(d[22]), "+f"(d[23]), "+f"(d[24]), "+f"(d[25]), "+f"(d[26]), "+f"(d[27]), "+f"(d[28]), "+f"(d[29]), "+f"(d[30]), "+f"(d[31])
    : "l"(da), "l"(db));
}
__device__ __forceinline__ void wgmma_ss0_n64_t00(float (&d)[32], uint64_t da, uint64_t db) {
  asm volatile("{\n.reg .pred p;\nsetp.ne.b32 p, 0, 0;\n"
    "wgmma.mma_async.sync.aligned.m64n64k16.f32.bf16.bf16 {%0, %1, %2, %3, %4, %5, %6, %7, %8, %9, %10, %11, %12, %13, %14, %15, %16, %17, %18, %19, %20, %21, %22, %23, %24, %25, %26, %27, %28, %29, %30, %31}, %32, %33, p, 1, 1, 0, 0;\n}\n"
    : "=f"(d[0]), "=f"(d[1]), "=f"(d[2]), "=f"(d[3]), "=f"(d[4]), "=f"(d[5]), "=f"(d[6]), "=f"(d[7]), "=f"(d[8]), "=f"(d[9]), "=f"(d[10]), "=f"(d[11]), "=f"(d[12]), "=f"(d[13]), "=f"(d[14]), "=f"(d[15]), "=f"(d[16]), "=f"(d[17]), "=f"(d[18]), "=f"(d[19]), "=f"(d[20]), "=f"(d[21]), "=f"(d[22]), "=f"(d[23]), "=f"(d[24]), "=f"(d[25]), "=f"(d[26]), "=f"(d[27]), "=f"(d[28]), "=f"(d[29]), "=f"(d[30]), "=f"(d[31])
    : "l"(da), "l"(db));
}
__device__ __forceinline__ void wgmma_rs_n24_t1(float (&d)[12], uint32_t a0, uint32_t a1, uint32_t a2, uint32_t a3, uint64_t db, int sd) {
  asm volatile("{\n.reg .pred p;\nsetp.ne.b32 p, %17, 0;\n"
    "wgmma.mma_async.sync.aligned.m64n24k16.f32.bf16.bf16 {%0, %1, %2, %3, %4, %5, %6, %7, %8, %9, %10, %11}, {%12, %13, %14, %15}, %16, p, 1, 1, 1;\n}\n"
    : "+f"(d[0]), "+f"(d[1]), "+f"(d[2]), "+f"(d[3]), "+f"(d[4]), "+f"(d[5]), "+f"(d[6]), "+f"(d[7]), "+f"(d[8]), "+f"(d[9]), "+f"(d[10]), "+f"(d[11])
    : "r"(a0), "r"(a1), "r"(a2), "r"(a3), "l"(db), "r"(sd));
}

constexpr int K1_NST = 4;
constexpr int NPROD = 2;
constexpr int K1_A_BYTES = 10 * 16384;
constexpr int K1_SMEM = K1_A_BYTES + K1_NST * 16384 + 1024 + 1024;

template <int BN, typename MMA>
__device__ __forceinline__ void k1_mainloop(float (&acc)[BN / 2], MMA mma, uint32_t sA, uint32_t sB, uint32_t barA, uint32_t barF,
                                            uint32_t barE, uint32_t barE_peer, int it0, bool waitA, int wgi, bool elect) {
  const uint64_t dA0 = mk_desc(sA + wgi * 8192, 16, 1024, 1);
  const uint64_t dB0 = mk_desc(sB, 4096, 1024, 1);
  fence_regs(acc);
#pragma unroll 1
  for (int s = 0; s < 20; s++) {
    const int it = it0 + s, st = it & (K1_NST - 1);
    if (waitA && !(s & 1)) mbar_wait(barA + 8 * (s >> 1), 0);
    mbar_wait(barF + 8 * st, (it / K1_NST) & 1);
    const uint64_t da = dA0 + (uint32_t)((s >> 1) * 1024 + (s & 1) * 4);
    const uint64_t db = dB0 + (uint32_t)(st * 1024);
    wg_fence();
    mma(acc, da, db, s);
    mma(acc, da + 2, db + 128, 1);
    wg_commit();
    if (s > 0) {
      wg_wait<1>();
      if (elect) { const int ps = (it - 1) & (K1_NST - 1); mbar_arrive_cluster(barE + 8 * ps); mbar_arrive_cluster(barE_peer + 8 * ps); }
    }
  }
  wg_wait<0>();
  fence_regs(acc);
  if (elect) { const int ps = (it0 + 19) & (K1_NST - 1); mbar_arrive_cluster(barE + 8 * ps); mbar_arrive_cluster(barE_peer + 8 * ps); }
}

__device__ __forceinline__ void st32(uint8_t* p, uint32_t v) { *reinterpret_cast<uint32_t*>(p) = v; }

template <int J0>
__device__ __forceinline__ void k1_qkv_epi(const float (&acc)[120], float (&nrm)[6], int slot0, int grp, int g, int t4) {
  const uint32_t tq = grp * 512 + g * 16, tkv = KV_OFF + grp * 768 + g * 16;
  const bool lo2 = t4 < 2;
  const uint32_t e0 = t4 * 4, e2 = lo2 ? 8 + t4 * 4 : 128 + (t4 - 2) * 4;
  const bool poly0 = !((MUFU_MASK >> (grp & 15)) & 1), poly1 = !((MUFU_MASK >> ((grp + 1) & 15)) & 1);
#pragma unroll
  for (int hp = 0; hp < 3; hp++) {
    uint8_t* ptr[2]; uint32_t gs[2]; float sc[2];
#pragma unroll
    for (int e = 0; e < 2; e++) {
      const int slot = slot0 + 2 * hp + e, which = slot >> 5, head = slot & 31;
      gs[e] = which == 0 ? 512u : 768u;
      sc[e] = which == 0 ? 0.32259642f : 1.0f;
      ptr[e] = g_QKV + (which == 0 ? head * 131072u + tq : head * 196608u + (which == 2 ? 384u : 0u) + tkv);
      if (t4 == 0) {
        uint2 c0, c1;
        if (which == 0) { c0 = make_uint2(0x42FB47C0u, 0x0000BDCCu); c1 = c0; }
        else if (which == 1) { c0 = poly0 ? make_uint2(0x3F803F80u, 0x00003F80u) : make_uint2(0u, 0u);
                               c1 = poly1 ? make_uint2(0x3F803F80u, 0x00003F80u) : make_uint2(0u, 0u); }
        else { c0 = make_uint2(0x00003F80u, 0u); c1 = c0; }
        *reinterpret_cast<uint2*>(ptr[e] + 264) = c0;
        *reinterpret_cast<uint2*>(ptr[e] + 264 + gs[e]) = c1;
      } else if (which == 0 && t4 < 3) {
        *reinterpret_cast<uint4*>(ptr[e] + 384 + (t4 - 1) * 512) = make_uint4(0, 0, 0, 0);
      }
    }
    const float scm = lo2 ? sc[0] : sc[1];
    uint8_t* pm = lo2 ? ptr[0] + 256 + e0 : ptr[1] + (e0 - 8);
    const uint32_t gm = lo2 ? gs[0] : gs[1];
    float q[5][2];
#pragma unroll
    for (int jj = 0; jj < 5; jj++) {
      const int j = J0 + hp * 5 + jj;
      const float f = jj < 2 ? sc[0] : (jj == 2 ? scm : sc[1]);
      const float v0 = acc[4 * j] * f, v1 = acc[4 * j + 1] * f, v2 = acc[4 * j + 2] * f, v3 = acc[4 * j + 3] * f;
      uint8_t* p = jj < 2 ? ptr[0] + jj * 128 + e0 : (jj == 2 ? pm : ptr[1] + (jj - 3) * 128 + e2);
      const uint32_t gg = jj < 2 ? gs[0] : (jj == 2 ? gm : gs[1]);
      st32(p, pack_bf16(v0, v1));
      st32(p + gg, pack_bf16(v2, v3));
      q[jj][0] = fmaf(v0, v0, v1 * v1);
      q[jj][1] = fmaf(v2, v2, v3 * v3);
    }
#pragma unroll
    for (int r = 0; r < 2; r++) {
      float a = q[0][r] + q[1][r] + (lo2 ? q[2][r] : 0.f), b = q[3][r] + q[4][r] + (lo2 ? 0.f : q[2][r]);
      a += __shfl_xor_sync(0xffffffffu, a, 1); b += __shfl_xor_sync(0xffffffffu, b, 1);
      a += __shfl_xor_sync(0xffffffffu, a, 2); b += __shfl_xor_sync(0xffffffffu, b, 2);
      nrm[2 * hp] = __uint_as_float(max(__float_as_uint(nrm[2 * hp]), __float_as_uint(a)));
      nrm[2 * hp + 1] = __uint_as_float(max(__float_as_uint(nrm[2 * hp + 1]), __float_as_uint(b)));
    }
  }
}

__global__ void __cluster_dims__(2, 1, 1) __launch_bounds__(384, 1)
k1_proj(const __grid_constant__ CUtensorMap tmX, const __grid_constant__ CUtensorMap tmWqkv, const __grid_constant__ CUtensorMap tmW1,
        const __nv_bfloat16* __restrict__ b1, const __nv_bfloat16* __restrict__ gate_w) {
  extern __shared__ uint8_t smem_raw[];
  const uint32_t sb = (smem_u32(smem_raw) + 1023u) & ~1023u;
  const uint32_t sA = sb, sB = sb + K1_A_BYTES, bars = sB + K1_NST * 16384;
  const uint32_t barA = bars, barF = bars + 80, barE = barF + 8 * K1_NST;
  const int tid = threadIdx.x, lane = tid & 31;
  const int warp = __shfl_sync(0xffffffffu, tid >> 5, 0);
  const int rb = blockIdx.x & 15, cg = blockIdx.x >> 4;
  const uint32_t rank = cluster_rank();
  if (tid == 0) {
    STAMP(0);
    prefetch_tmap(&tmX); prefetch_tmap(&tmWqkv); prefetch_tmap(&tmW1);
    for (int i = 0; i < 10; i++) mbar_init(barA + 8 * i, 1);
    for (int i = 0; i < K1_NST; i++) { mbar_init(barF + 8 * i, 1); mbar_init(barE + 8 * i, 16); }
    fence_barrier_init();
    fence_proxy_async();
    for (int kb = 0; kb < 2; kb++) {
      mbar_expect_tx(barA + 8 * kb, 16384);
      tma_2d(sA + kb * 16384, &tmX, kb * 64, rb * 128, barA + 8 * kb);
    }
  }
  pdl_launch();
  __syncwarp();
  cluster_arrive();
  cluster_wait();

  if (warp < 4) {
    if (warp == 0 || warp == 2) {
      if (lane == 0) {
#pragma unroll 1
        for (int it = warp >> 1; it < 40; it += NPROD) {
          const int st = it & (K1_NST - 1);
          const bool t0 = it < 20;
          const CUtensorMap* m = t0 ? &tmWqkv : &tmW1;
          const int col = (t0 ? cg * 240 : cg * 216) + (int)rank * 128;
          const int k = (t0 ? it : it - 20) * 32;
          const uint32_t dst = sB + st * 16384 + rank * 8192;
          if (it >= K1_NST) mbar_wait(barE + 8 * st, ((it / K1_NST) - 1) & 1);
          mbar_expect_tx(barF + 8 * st, 16384);
          tma_2d_mc(dst, m, col, k, barF + 8 * st, (uint16_t)3);
          tma_2d_mc(dst + 4096, m, col + 64, k, barF + 8 * st, (uint16_t)3);
          if (it < 16 && (it & 1)) {
            const int ka = (it >> 1) + 2;
            mbar_expect_tx(barA + 8 * ka, 16384);
            tma_2d(sA + ka * 16384, &tmX, ka * 64, rb * 128, barA + 8 * ka);
          }
        }
      }
    } else if (warp == 1) {
      const int r = cg * 16 + (lane >> 1), half = lane & 1;
      float acc = 0.f;
      mbar_wait(barA + 72, 0);
#pragma unroll 1
      for (int kb = half * 5; kb < half * 5 + 5; kb++) {
        mbar_wait(barA + 8 * kb, 0);
#pragma unroll
        for (int c = 0; c < 8; c++) {
          uint4 xv;
          asm volatile("ld.shared.v4.u32 {%0,%1,%2,%3}, [%4];" : "=r"(xv.x), "=r"(xv.y), "=r"(xv.z), "=r"(xv.w)
                       : "r"(sA + kb * 16384 + r * 128 + ((c ^ (r & 7)) << 4)));
          const uint4 wv = __ldg(reinterpret_cast<const uint4*>(gate_w + kb * 64 + c * 8));
          acc = fmaf(bf_lo(xv.x), bf_lo(wv.x), acc); acc = fmaf(bf_hi(xv.x), bf_hi(wv.x), acc);
          acc = fmaf(bf_lo(xv.y), bf_lo(wv.y), acc); acc = fmaf(bf_hi(xv.y), bf_hi(wv.y), acc);
          acc = fmaf(bf_lo(xv.z), bf_lo(wv.z), acc); acc = fmaf(bf_hi(xv.z), bf_hi(wv.z), acc);
          acc = fmaf(bf_lo(xv.w), bf_lo(wv.w), acc); acc = fmaf(bf_hi(xv.w), bf_hi(wv.w), acc);
        }
      }
      acc += __shfl_xor_sync(0xffffffffu, acc, 1);
      if (!half) g_gate[rb * 128 + r] = 1.f / (1.f + __expf(-acc));
    }
  } else {
    const int wgi = (warp >> 2) - 1, wq = warp & 3, g = lane >> 2, t4 = lane & 3;
    const uint32_t barE_self = mapa(barE, rank), barE_peer = mapa(barE, rank ^ 1);
    const bool elect = lane == 0;
    {
      float acc[120];
      k1_mainloop<240>(acc, [](float (&d)[120], uint64_t a, uint64_t b, int sd) { wgmma_ssp_n240_t01(d, a, b, sd); },
                       sA, sB, barA, barF, barE_self, barE_peer, 0, true, wgi, elect);
      if (warp == 4) STAMP(1);
      const int grp = rb * 16 + wgi * 8 + wq * 2;
#pragma unroll
      for (int half = 0; half < 2; half++) {
        float nrm[6] = {0.f, 0.f, 0.f, 0.f, 0.f, 0.f};
        const int slot0 = cg * 12 + half * 6;
        if (half == 0) k1_qkv_epi<0>(acc, nrm, slot0, grp, g, t4); else k1_qkv_epi<15>(acc, nrm, slot0, grp, g, t4);
#pragma unroll
        for (int h = 0; h < 6; h++) {
          const uint32_t m = __reduce_max_sync(0xffffffffu, __float_as_uint(nrm[h]));
          if (lane == h) g_norm[(slot0 + h) * 128 + rb * 8 + wgi * 4 + wq] = __uint_as_float(m);
        }
      }
    }
    if (warp == 4) STAMP(2);
    {
      float acc[108];
      k1_mainloop<216>(acc, [](float (&d)[108], uint64_t a, uint64_t b, int sd) { wgmma_ssp_n216_t01(d, a, b, sd); },
                       sA, sB, barA, barF, barE_self, barE_peer, 20, false, wgi, elect);
      if (warp == 8) STAMP(3);
      uint8_t* base = g_A2 + ((size_t)(rb * 296 + cg * 27) * 16 + wgi * 8 + wq * 2) * 128 + g * 16 + t4 * 4;
      const uint32_t* bp = reinterpret_cast<const uint32_t*>(b1 + cg * 216 + t4 * 2);
#pragma unroll
      for (int j = 0; j < 27; j++) {
        const uint32_t bv = __ldg(bp + j * 4);
        const float c0 = bf_lo(bv), c1 = bf_hi(bv);
        const float h0 = fmaxf(acc[4 * j] + c0, 0.f), h1 = fmaxf(acc[4 * j + 1] + c1, 0.f);
        const float h2 = fmaxf(acc[4 * j + 2] + c0, 0.f), h3 = fmaxf(acc[4 * j + 3] + c1, 0.f);
        st32(base + j * 2048, pack_bf16(h0 * h0, h1 * h1));
        st32(base + j * 2048 + 128, pack_bf16(h2 * h2, h3 * h3));
      }
    }
    if (warp == 8) STAMP(4);
  }
  __syncwarp();
  cluster_arrive_relaxed();
  cluster_wait();
}

constexpr int KV_HEAD_BYTES = 256 * 768, Q_BYTES = 8 * 4096;
constexpr int AT_NCHUNK = 16, AT_CHUNK_BYTES = KV_HEAD_BYTES / AT_NCHUNK;
constexpr int AT_SMEM = KV_HEAD_BYTES + Q_BYTES + 1024 + 1024;

template <int T0, int T1, int TOFF>
__device__ __forceinline__ void exp_tiles(const float (&s)[32], uint32_t (&p)[16], uint32_t cmask, uint32_t cone) {
#pragma unroll
  for (int t = T0; t < T1; t++) {
#pragma unroll
    for (int h = 0; h < 2; h++) {
      const float x0 = s[4 * t + 2 * h], x1 = s[4 * t + 2 * h + 1];
      uint32_t r;
      if ((MUFU_MASK >> ((t + TOFF) & 15)) & 1) {
        r = pack_bf16(ex2(x0), ex2(x1));
      } else {
        const uint32_t u = __byte_perm(__float_as_uint(x0), __float_as_uint(x1), 0x5410);
        uint32_t g;
        asm("lop3.b32 %0, %1, %2, %3, 0xEA;" : "=r"(g) : "r"(u), "r"(cmask), "r"(cone));
        r = hfma2_bf16(g, g, 0x40034003u) + u - g;
      }
      p[2 * t + h] = r;
      asm volatile("" : "+r"(p[2 * t + h])::"memory");
    }
  }
}
template <int TOFF>
__device__ __forceinline__ void exp_pv(const float (&s)[32], uint32_t (&p)[16], float (&o)[12], uint64_t dv, int sd, uint32_t cmask, uint32_t cone) {
  exp_tiles<0, 4, TOFF>(s, p, cmask, cone);
  wg_fence();
  wgmma_rs_n24_t1(o, p[0], p[1], p[2], p[3], dv, sd);
  wgmma_rs_n24_t1(o, p[4], p[5], p[6], p[7], dv + 96, 1);
  exp_tiles<4, 8, TOFF>(s, p, cmask, cone);
  wg_fence();
  wgmma_rs_n24_t1(o, p[8], p[9], p[10], p[11], dv + 192, 1);
  wgmma_rs_n24_t1(o, p[12], p[13], p[14], p[15], dv + 288, 1);
}
__device__ __forceinline__ void qk64(float (&s)[32], uint64_t dq, uint64_t dk) {
  wgmma_ss0_n64_t00(s, dq, dk);
  wgmma_ss_n64_t00(s, dq + 16, dk + 16);
}
__device__ __forceinline__ void attn_store(const float (&o)[12], int row0, int head, int lane) {
  const int t4 = lane & 3;
  const float l0 = __shfl_sync(0xffffffffu, o[8], (lane & ~3) | 2), l1 = __shfl_sync(0xffffffffu, o[10], (lane & ~3) | 2);
  const float r0 = __fdividef(g_gate[row0], l0), r1 = __fdividef(g_gate[row0 + 8], l1);
  uint8_t* base = g_A2 + ((size_t)((row0 >> 7) * 296 + 216) * 16 + ((row0 & 127) >> 3)) * 128 + (row0 & 7) * 16;
#pragma unroll
  for (int tt = 0; tt < 3; tt++) {
    const int d = tt * 8 + 2 * t4;
    if (d < 20) {
      const int col = head * 20 + d;
      uint8_t* ptr = base + (col >> 3) * 2048 + (col & 7) * 2;
      *reinterpret_cast<uint32_t*>(ptr) = pack_bf16(o[4 * tt] * r0, o[4 * tt + 1] * r0);
      *reinterpret_cast<uint32_t*>(ptr + 128) = pack_bf16(o[4 * tt + 2] * r1, o[4 * tt + 3] * r1);
    }
  }
}

__device__ __forceinline__ void attn_slow(uint32_t sb, uint32_t bb, int wg, int rowbase, int head, int lane) {
  const uint64_t dk0 = mk_desc(sb, 128, 768, 0), dv0 = mk_desc(sb + 384, 768, 128, 0);
  const uint64_t dq0 = mk_desc(sb + KV_HEAD_BYTES + wg * 8192, 128, 512, 0);
#pragma unroll 1
  for (int mt = 0; mt < 2; mt++) {
    float o[12], s[32];
    uint32_t p[16];
#pragma unroll
    for (int i = 0; i < 12; i++) o[i] = 0.f;
    float m0 = -INFINITY, m1 = -INFINITY;
#pragma unroll 1
    for (int b = 0; b < 32; b++) {
      if (mt == 0 && !(b & 1)) mbar_wait(bb + 8 * (b >> 1), 0);
      wg_fence();
      qk64(s, dq0 + (uint32_t)(mt * 256), dk0 + (uint32_t)(b * 384));
      wg_commit();
      wg_wait<0>();
      fence_regs(s);
      float n0 = m0, n1 = m1;
#pragma unroll
      for (int t = 0; t < 8; t++) { n0 = fmaxf(n0, fmaxf(s[4 * t], s[4 * t + 1])); n1 = fmaxf(n1, fmaxf(s[4 * t + 2], s[4 * t + 3])); }
      n0 = fmaxf(n0, __shfl_xor_sync(0xffffffffu, n0, 1)); n0 = fmaxf(n0, __shfl_xor_sync(0xffffffffu, n0, 2));
      n1 = fmaxf(n1, __shfl_xor_sync(0xffffffffu, n1, 1)); n1 = fmaxf(n1, __shfl_xor_sync(0xffffffffu, n1, 2));
      const float a0 = ex2(m0 - n0), a1 = ex2(m1 - n1);
      m0 = n0; m1 = n1;
#pragma unroll
      for (int t = 0; t < 3; t++) { o[4 * t] *= a0; o[4 * t + 1] *= a0; o[4 * t + 2] *= a1; o[4 * t + 3] *= a1; }
#pragma unroll
      for (int t = 0; t < 8; t++) {
        p[2 * t] = pack_bf16(ex2(s[4 * t] - m0), ex2(s[4 * t + 1] - m0));
        p[2 * t + 1] = pack_bf16(ex2(s[4 * t + 2] - m1), ex2(s[4 * t + 3] - m1));
      }
      fence_regs(o);
      wg_fence();
#pragma unroll
      for (int k = 0; k < 4; k++) wgmma_rs_n24_t1(o, p[4 * k], p[4 * k + 1], p[4 * k + 2], p[4 * k + 3], dv0 + (uint32_t)(b * 384 + k * 96), 1);
      wg_commit();
      wg_wait<0>();
      fence_regs(o);
    }
    attn_store(o, rowbase + mt * 64, head, lane);
  }
}

__global__ void __launch_bounds__(512, 1) k2_attn(int opaque_zero) {
  extern __shared__ uint8_t smem_raw[];
  const uint32_t sb = (smem_u32(smem_raw) + 1023u) & ~1023u;
  const uint32_t bb = sb + KV_HEAD_BYTES + Q_BYTES;
  const int tid = threadIdx.x, lane = tid & 31;
  const int warp = __shfl_sync(0xffffffffu, tid >> 5, 0), wg = warp >> 2;
  const int head = blockIdx.x >> 2, qb = blockIdx.x & 3;
  if (tid == 0) {
    STAMP(5);
    for (int i = 0; i <= AT_NCHUNK; i++) mbar_init(bb + 8 * i, 1);
    fence_barrier_init();
    fence_proxy_async();
  }
  pdl_launch();
  pdl_wait();
  if (tid == 0) {
    STAMP(6);
    mbar_expect_tx(bb + 8 * AT_NCHUNK, Q_BYTES);
    bulk_g2s(sb + KV_HEAD_BYTES, g_QKV + (size_t)blockIdx.x * Q_BYTES, Q_BYTES, bb + 8 * AT_NCHUNK);
    for (int i = 0; i < AT_NCHUNK; i++) {
      mbar_expect_tx(bb + 8 * i, AT_CHUNK_BYTES);
      bulk_g2s(sb + i * AT_CHUNK_BYTES, g_QKV + KV_OFF + (size_t)head * KV_HEAD_BYTES + i * AT_CHUNK_BYTES, AT_CHUNK_BYTES, bb + 8 * i);
    }
  }
  bool fast;
  {
    const uint32_t* nb = reinterpret_cast<const uint32_t*>(g_norm);
    const uint4 k4 = *reinterpret_cast<const uint4*>(nb + (32 + head) * 128 + lane * 4);
    const uint4 v4 = *reinterpret_cast<const uint4*>(nb + (64 + head) * 128 + lane * 4);
    const float nq = __uint_as_float(__reduce_max_sync(0xffffffffu, nb[head * 128 + qb * 32 + lane]));
    const float nk = __uint_as_float(__reduce_max_sync(0xffffffffu, max(max(k4.x, k4.y), max(k4.z, k4.w))));
    const float nv = __uint_as_float(__reduce_max_sync(0xffffffffu, max(max(v4.x, v4.y), max(v4.z, v4.w))));
    fast = (nq * nk <= 2304.0f) && (nq <= 1e30f) && (nk <= 1e30f) && (nv <= 1e30f) && (nv >= 1e-18f);
  }
  const int rowbase = qb * 512 + wg * 128 + (warp & 3) * 16 + (lane >> 2);
  __syncthreads();
  mbar_wait(bb + 8 * AT_NCHUNK, 0);
  if (!fast) {
    *reinterpret_cast<uint2*>(smem_raw + (sb - smem_u32(smem_raw)) + KV_HEAD_BYTES + (tid >> 3) * 512 + 256 + (tid & 7) * 16 + 8) = make_uint2(0u, 0u);
    fence_proxy_async();
    __syncthreads();
    attn_slow(sb, bb, wg, rowbase, head, lane);
    return;
  }
  uint32_t cmask = 0x007F007Fu + opaque_zero, cone = 0x3F803F80u + opaque_zero;
  const uint64_t dk0 = mk_desc(sb, 128, 768, 0), dv0 = mk_desc(sb + 384, 768, 128, 0);
  const uint64_t dq0 = mk_desc(sb + KV_HEAD_BYTES + wg * 8192, 128, 512, 0);
  float o[12], s0[32], s1[32];
  uint32_t p0[16], p1[16];
#pragma unroll
  for (int i = 0; i < 12; i++) o[i] = 0.f;
  fence_regs(o);
  mbar_wait(bb, 0);
  wg_fence();
  qk64(s0, dq0, dk0);
  wg_commit();
  wg_wait<0>();
  fence_regs(s0);
#pragma unroll 1
  for (int it = 0; it < 32; it++) {
    const int c = it & 15, mt = it >> 4;
    const uint64_t dq = dq0 + (uint32_t)(mt * 256);
    const uint32_t off = c * 768;
    wg_fence();
    qk64(s1, dq, dk0 + (off + 384));
    wg_commit();
    exp_pv<0>(s0, p0, o, dv0 + off, c, cmask, cone);
    wg_commit();
    wg_wait<1>();
    fence_regs(s1);
    const int cn = (c + 1) & 15;
    const uint64_t dqn = dq0 + (uint32_t)((((it + 1) >> 4) & 1) * 256);
    if (it < 15) mbar_wait(bb + 8 * cn, 0);
    wg_fence();
    qk64(s0, dqn, dk0 + (uint32_t)(cn * 768));
    wg_commit();
    exp_pv<8>(s1, p1, o, dv0 + (off + 384), 1, cmask, cone);
    wg_commit();
    wg_wait<0>();
    fence_regs(s0);
    fence_regs(o);
    if (c == 15) attn_store(o, rowbase + mt * 64, head, lane);
  }
  if (warp == 0) STAMP(8);
}

constexpr int K3_NST = 8, K3_STAGE = 8192 + 10240;
constexpr int K3_RED = 128 * 80 * 4;
constexpr int K3_SMEM = K3_NST * K3_STAGE + K3_RED + 1024 + 1024;

__global__ void __cluster_dims__(2, 1, 1) __launch_bounds__(288, 1)
k3_out(const __grid_constant__ CUtensorMap tmW2, const __grid_constant__ CUtensorMap tmWo, const __nv_bfloat16* __restrict__ b2,
       __nv_bfloat16* __restrict__ out) {
  extern __shared__ uint8_t smem_raw[];
  const uint32_t sb = (smem_u32(smem_raw) + 1023u) & ~1023u;
  const uint32_t sRed = sb + K3_NST * K3_STAGE, barF = sRed + K3_RED, barE = barF + 8 * K3_NST, barR = barE + 8 * K3_NST;
  const int tid = threadIdx.x, lane = tid & 31;
  const int warp = __shfl_sync(0xffffffffu, tid >> 5, 0);
  const uint32_t rank = cluster_rank();
  const int tile = blockIdx.x >> 1, rb = tile >> 2, ct = tile & 3;
  if (tid == 0) {
    STAMP(9);
    prefetch_tmap(&tmW2); prefetch_tmap(&tmWo);
    for (int i = 0; i < K3_NST; i++) { mbar_init(barF + 8 * i, 1); mbar_init(barE + 8 * i, 8); }
    mbar_init(barR, 1);
    fence_barrier_init();
    mbar_expect_tx(barR, K3_RED);
  }
  __syncwarp();
  cluster_arrive();
  cluster_wait();
  if (warp == 8) {
    if (lane == 0) {
      const int s0 = rank * 37;
      const uint8_t* asrc = g_A2 + (size_t)rb * 296 * 2048;
      for (int i = 0; i < K3_NST; i++) {
        const int s = s0 + i;
        mbar_expect_tx(barF + 8 * i, K3_STAGE);
        for (int b = 0; b < 5; b++) tma_2d(sb + i * K3_STAGE + 8192 + b * 2048, &tmW2, ct * 160 + b * 32, s * 32, barF + 8 * i);
      }
      pdl_wait();
      for (int i = 0; i < K3_NST; i++) bulk_g2s(sb + i * K3_STAGE, asrc + (size_t)(s0 + i) * 8192, 8192, barF + 8 * i);
#pragma unroll 1
      for (int i = K3_NST; i < 37; i++) {
        const int st = i & (K3_NST - 1), s = s0 + i;
        mbar_wait(barE + 8 * st, ((i / K3_NST) - 1) & 1);
        mbar_expect_tx(barF + 8 * st, K3_STAGE);
        bulk_g2s(sb + st * K3_STAGE, asrc + (size_t)s * 8192, 8192, barF + 8 * st);
        const CUtensorMap* m = s < 54 ? &tmW2 : &tmWo;
        const int k = (s < 54 ? s : s - 54) * 32;
        for (int b = 0; b < 5; b++) tma_2d(sb + st * K3_STAGE + 8192 + b * 2048, m, ct * 160 + b * 32, k, barF + 8 * st);
      }
    }
  } else {
    const int wgi = warp >> 2, wq = warp & 3, g = lane >> 2, t4 = lane & 3;
    const int rloc = wgi * 64 + wq * 16 + g, row = rb * 128 + rloc;
    const int col0 = ct * 160 + rank * 80 + t4 * 2;
    uint32_t bias[10];
#pragma unroll
    for (int j = 0; j < 10; j++) bias[j] = __ldg(reinterpret_cast<const uint32_t*>(b2 + col0 + j * 8));
    pdl_wait();
    if (warp == 0) STAMP(10);
    const float w0 = 1.f - g_gate[row], w1 = 1.f - g_gate[row + 8];
    float acc[80];
    const uint64_t dA0 = mk_desc(sb + wgi * 1024, 2048, 128, 0), dB0 = mk_desc(sb + 8192, 2048, 512, 2);
    const int nsw = rank ? 17 : 37;
    fence_regs(acc);
#pragma unroll 1
    for (int i = 0; i < 37; i++) {
      const int st = i & (K3_NST - 1);
      mbar_wait(barF + 8 * st, (i / K3_NST) & 1);
      const uint32_t off = st * (K3_STAGE >> 4);
      wg_fence();
      wgmma_ssp_n160_t01(acc, dA0 + off, dB0 + off, i);
      wgmma_ssp_n160_t01(acc, dA0 + off + 256, dB0 + off + 64, 1);
      wg_commit();
      if (i + 1 == nsw) {
        wg_wait<0>();
        fence_regs(acc);
#pragma unroll
        for (int j = 0; j < 20; j++) { acc[4 * j] *= w0; acc[4 * j + 1] *= w0; acc[4 * j + 2] *= w1; acc[4 * j + 3] *= w1; }
        fence_regs(acc);
      } else {
        wg_wait<1>();
      }
      if (i > 0 && lane == 0) mbar_arrive(barE + 8 * ((i - 1) & (K3_NST - 1)));
    }
    wg_wait<0>();
    fence_regs(acc);
    if (warp == 0) STAMP(11);
    const uint32_t peerRed = mapa(sRed, rank ^ 1) + tid * 16, peerBar = mapa(barR, rank ^ 1);
#pragma unroll
    for (int j = 0; j < 10; j++) {
      const float a0 = rank ? acc[4 * j] : acc[40 + 4 * j], a1 = rank ? acc[4 * j + 1] : acc[40 + 4 * j + 1];
      const float a2 = rank ? acc[4 * j + 2] : acc[40 + 4 * j + 2], a3 = rank ? acc[4 * j + 3] : acc[40 + 4 * j + 3];
      asm volatile("st.async.weak.shared::cluster.mbarrier::complete_tx::bytes.v4.f32 [%0], {%1, %2, %3, %4}, [%5];"
                   ::"r"(peerRed + j * 4096), "f"(a0), "f"(a1), "f"(a2), "f"(a3), "r"(peerBar) : "memory");
    }
    mbar_wait(barR, 0);
    if (warp == 0) STAMP(13);
#pragma unroll
    for (int j = 0; j < 10; j++) {
      float p0, p1, p2, p3;
      asm volatile("ld.shared.v4.f32 {%0, %1, %2, %3}, [%4];" : "=f"(p0), "=f"(p1), "=f"(p2), "=f"(p3) : "r"(sRed + tid * 16 + j * 4096));
      const float a0 = rank ? acc[40 + 4 * j] : acc[4 * j], a1 = rank ? acc[40 + 4 * j + 1] : acc[4 * j + 1];
      const float a2 = rank ? acc[40 + 4 * j + 2] : acc[4 * j + 2], a3 = rank ? acc[40 + 4 * j + 3] : acc[4 * j + 3];
      const float c0 = bf_lo(bias[j]), c1 = bf_hi(bias[j]);
      *reinterpret_cast<uint32_t*>(out + (size_t)row * D_ + col0 + j * 8) = pack_bf16(fmaf(w0, c0, a0 + p0), fmaf(w0, c1, a1 + p1));
      *reinterpret_cast<uint32_t*>(out + (size_t)(row + 8) * D_ + col0 + j * 8) = pack_bf16(fmaf(w1, c0, a2 + p2), fmaf(w1, c1, a3 + p3));
    }
    if (warp == 0) STAMP(12);
  }
}

typedef CUresult (*EncodeFn)(CUtensorMap*, CUtensorMapDataType, cuuint32_t, void*, const cuuint64_t*, const cuuint64_t*, const cuuint32_t*,
                             const cuuint32_t*, CUtensorMapInterleave, CUtensorMapSwizzle, CUtensorMapL2promotion, CUtensorMapFloatOOBfill);

void make_map(EncodeFn fn, CUtensorMap* m, const void* ptr, uint64_t inner, uint64_t outer, uint32_t box_inner, uint32_t box_outer, CUtensorMapSwizzle sw) {
  cuuint64_t dims[2] = {inner, outer};
  cuuint64_t strides[1] = {inner * 2};
  cuuint32_t box[2] = {box_inner, box_outer};
  cuuint32_t es[2] = {1, 1};
  fn(m, CU_TENSOR_MAP_DATA_TYPE_BFLOAT16, 2, const_cast<void*>(ptr), dims, strides, box, es, CU_TENSOR_MAP_INTERLEAVE_NONE, sw,
     CU_TENSOR_MAP_L2_PROMOTION_L2_256B, CU_TENSOR_MAP_FLOAT_OOB_FILL_NONE);
}

}

extern "C" void kernel_launch(void* const* d_in, const int* in_sizes, int n_in, void* d_out, int out_size) {
  (void)in_sizes; (void)n_in; (void)out_size;
  const __nv_bfloat16* x = (const __nv_bfloat16*)d_in[0];
  const __nv_bfloat16* wqkv = (const __nv_bfloat16*)d_in[1];
  const __nv_bfloat16* wo = (const __nv_bfloat16*)d_in[2];
  const __nv_bfloat16* w1 = (const __nv_bfloat16*)d_in[4];
  const __nv_bfloat16* b1 = (const __nv_bfloat16*)d_in[5];
  const __nv_bfloat16* w2 = (const __nv_bfloat16*)d_in[6];
  const __nv_bfloat16* b2 = (const __nv_bfloat16*)d_in[7];
  const __nv_bfloat16* gw = (const __nv_bfloat16*)d_in[8];

  static EncodeFn enc = nullptr;
  if (!enc) {
    void* p = nullptr;
    cudaDriverEntryPointQueryResult qr;
    cudaGetDriverEntryPoint("cuTensorMapEncodeTiled", &p, cudaEnableDefault, &qr);
    enc = (EncodeFn)p;
    cudaFuncSetAttribute(k1_proj, cudaFuncAttributeMaxDynamicSharedMemorySize, K1_SMEM);
    cudaFuncSetAttribute(k2_attn, cudaFuncAttributeMaxDynamicSharedMemorySize, AT_SMEM);
    cudaFuncSetAttribute(k3_out, cudaFuncAttributeMaxDynamicSharedMemorySize, K3_SMEM);
  }
  CUtensorMap tmX, tmWqkv, tmW1, tmW2, tmWo;
  make_map(enc, &tmX, x, D_, S_, 64, 128, CU_TENSOR_MAP_SWIZZLE_128B);
  make_map(enc, &tmWqkv, wqkv, 3 * D_, D_, 64, 32, CU_TENSOR_MAP_SWIZZLE_128B);
  make_map(enc, &tmW1, w1, F_, D_, 64, 32, CU_TENSOR_MAP_SWIZZLE_128B);
  make_map(enc, &tmW2, w2, D_, F_, 32, 32, CU_TENSOR_MAP_SWIZZLE_64B);
  make_map(enc, &tmWo, wo, D_, D_, 32, 32, CU_TENSOR_MAP_SWIZZLE_64B);

  cudaStream_t st = cudaStreamPerThread;
  k1_proj<<<128, 384, K1_SMEM, st>>>(tmX, tmWqkv, tmW1, b1, gw);

  cudaLaunchAttribute at[1];
  at[0].id = cudaLaunchAttributeProgrammaticStreamSerialization;
  at[0].val.programmaticStreamSerializationAllowed = 1;
  {
    cudaLaunchConfig_t cfg = {};
    cfg.gridDim = dim3(128); cfg.blockDim = dim3(512); cfg.dynamicSmemBytes = AT_SMEM; cfg.stream = st;
    cfg.attrs = at; cfg.numAttrs = 1;
    cudaLaunchKernelEx(&cfg, k2_attn, 0);
  }
  {
    cudaLaunchConfig_t cfg = {};
    cfg.gridDim = dim3(128); cfg.blockDim = dim3(288); cfg.dynamicSmemBytes = K3_SMEM; cfg.stream = st;
    cfg.attrs = at; cfg.numAttrs = 1;
    cudaLaunchKernelEx(&cfg, k3_out, tmW2, tmWo, b2, (__nv_bfloat16*)d_out);
  }
}
```

```cpp
#include <cuda_runtime.h>
#include <cuda_bf16.h>
#include <cuda.h>
#include <stdint.h>

namespace {

constexpr int S_ = 2048, D_ = 640, NH = 32, F_ = 1728;

constexpr uint32_t KV_OFF = NH * 256 * 512;
__device__ __align__(1024) uint8_t g_QKV[NH * 256 * 512 + NH * 256 * 768];
__device__ __align__(1024) uint8_t g_A2[16 * 296 * 2048];
__device__ float g_gate[S_];
__device__ __align__(16) float g_norm[96 * 128];

constexpr uint32_t MUFU_MASK = 0x5151u;

#define STAMP(i) do { } while (0)

__device__ __forceinline__ uint32_t smem_u32(const void* p) { return (uint32_t)__cvta_generic_to_shared(p); }
__device__ __forceinline__ void wg_fence() { asm volatile("wgmma.fence.sync.aligned;" ::: "memory"); }
__device__ __forceinline__ void wg_commit() { asm volatile("wgmma.commit_group.sync.aligned;" ::: "memory"); }
template <int N> __device__ __forceinline__ void wg_wait() { asm volatile("wgmma.wait_group.sync.aligned %0;" ::"n"(N) : "memory"); }
template <int N> __device__ __forceinline__ void fence_regs(float (&r)[N]) {
#pragma unroll
  for (int i = 0; i < N; i++) asm volatile("" : "+f"(r[i])::"memory");
}
__device__ __forceinline__ float ex2(float x) { float y; asm("ex2.approx.ftz.f32 %0, %1;" : "=f"(y) : "f"(x)); return y; }
__device__ __forceinline__ uint32_t pack_bf16(float lo, float hi) { uint32_t y; asm("cvt.rn.bf16x2.f32 %0, %1, %2;" : "=r"(y) : "f"(hi), "f"(lo)); return y; }
__device__ __forceinline__ uint32_t hfma2_bf16(uint32_t a, uint32_t b, uint32_t c) { uint32_t y; asm("fma.rn.bf16x2 %0, %1, %2, %3;" : "=r"(y) : "r"(a), "r"(b), "r"(c)); return y; }
__device__ __forceinline__ float bf_lo(uint32_t v) { return __uint_as_float(v << 16); }
__device__ __forceinline__ float bf_hi(uint32_t v) { return __uint_as_float(v & 0xffff0000u); }
__device__ __forceinline__ void mbar_init(uint32_t bar, int cnt) { asm volatile("mbarrier.init.shared::cta.b64 [%0], %1;" ::"r"(bar), "r"(cnt)); }
__device__ __forceinline__ void mbar_expect_tx(uint32_t bar, uint32_t bytes) { asm volatile("mbarrier.arrive.expect_tx.shared::cta.b64 _, [%0], %1;" ::"r"(bar), "r"(bytes) : "memory"); }
__device__ __forceinline__ void mbar_arrive(uint32_t bar) { asm volatile("mbarrier.arrive.shared::cta.b64 _, [%0];" ::"r"(bar) : "memory"); }
__device__ __forceinline__ void mbar_arrive_cluster(uint32_t cluster_addr) { asm volatile("mbarrier.arrive.shared::cluster.b64 _, [%0];" ::"r"(cluster_addr) : "memory"); }
__device__ __forceinline__ void mbar_wait(uint32_t bar, uint32_t parity) {
  asm volatile(
      "{\n.reg .pred p;\n.reg .u32 n;\n"
      "mbarrier.try_wait.parity.shared::cta.b64 p, [%0], %1;\n"
      "@p bra DONE;\n"
      "mov.u32 n, 0;\n"
      "LOOP:\n"
      "mbarrier.try_wait.parity.shared::cta.b64 p, [%0], %1;\n"
      "@p bra DONE;\n"
      "add.u32 n, n, 1;\n"
      "setp.lt.u32 p, n, 0x1000000;\n"
      "@p bra LOOP;\n"
      "trap;\n"
      "DONE:\n}\n" ::"r"(bar), "r"(parity) : "memory");
}
__device__ __forceinline__ void bulk_g2s(uint32_t dst, const void* src, uint32_t bytes, uint32_t bar) {
  asm volatile("cp.async.bulk.shared::cluster.global.mbarrier::complete_tx::bytes [%0], [%1], %2, [%3];" ::"r"(dst), "l"(src), "r"(bytes), "r"(bar) : "memory");
}
__device__ __forceinline__ void l2_prefetch(const void* src, uint32_t bytes) {
  asm volatile("cp.async.bulk.prefetch.L2.global [%0], %1;" ::"l"(src), "r"(bytes) : "memory");
}
__device__ __forceinline__ void tma_2d(uint32_t dst, const CUtensorMap* m, int c0, int c1, uint32_t bar) {
  asm volatile("cp.async.bulk.tensor.2d.shared::cluster.global.mbarrier::complete_tx::bytes [%0], [%1, {%3, %4}], [%2];" ::"r"(dst), "l"(m), "r"(bar), "r"(c0), "r"(c1) : "memory");
}
__device__ __forceinline__ void tma_2d_mc(uint32_t dst, const CUtensorMap* m, int c0, int c1, uint32_t bar, uint16_t mask) {
  asm volatile("cp.async.bulk.tensor.2d.shared::cluster.global.mbarrier::complete_tx::bytes.multicast::cluster [%0], [%1, {%3, %4}], [%2], %5;" ::"r"(dst), "l"(m), "r"(bar), "r"(c0), "r"(c1), "h"(mask) : "memory");
}
__device__ __forceinline__ uint32_t mapa(uint32_t addr, uint32_t rank) { uint32_t r; asm("mapa.shared::cluster.u32 %0, %1, %2;" : "=r"(r) : "r"(addr), "r"(rank)); return r; }
__device__ __forceinline__ uint32_t cluster_rank() { uint32_t r; asm("mov.u32 %0, %%cluster_ctarank;" : "=r"(r)); return r; }
__device__ __forceinline__ void cluster_arrive() { asm volatile("barrier.cluster.arrive.release.aligned;" ::: "memory"); }
__device__ __forceinline__ void cluster_arrive_relaxed() { asm volatile("barrier.cluster.arrive.relaxed.aligned;" ::: "memory"); }
__device__ __forceinline__ void cluster_wait() { asm volatile("barrier.cluster.wait.acquire.aligned;" ::: "memory"); }
__device__ __forceinline__ void bar_sync(int id, int n) { asm volatile("bar.sync %0, %1;" ::"r"(id), "r"(n) : "memory"); }
__device__ __forceinline__ void bar_arrive(int id, int n) { asm volatile("bar.arrive %0, %1;" ::"r"(id), "r"(n) : "memory"); }
__device__ __forceinline__ void pdl_launch() { asm volatile("griddepcontrol.launch_dependents;" ::: "memory"); }
__device__ __forceinline__ void pdl_wait() { asm volatile("griddepcontrol.wait;" ::: "memory"); }
__device__ __forceinline__ void fence_barrier_init() { asm volatile("fence.mbarrier_init.release.cluster;" ::: "memory"); }
__device__ __forceinline__ void fence_proxy_async() { asm volatile("fence.proxy.async.shared::cta;" ::: "memory"); }
__device__ __forceinline__ void prefetch_tmap(const CUtensorMap* m) { asm volatile("prefetch.tensormap [%0];" ::"l"(m) : "memory"); }
__device__ __forceinline__ uint64_t mk_desc(uint32_t addr, uint32_t lbo, uint32_t sbo, uint32_t mode) {
  return (uint64_t)((addr & 0x3FFFF) >> 4) | ((uint64_t)(lbo >> 4) << 16) | ((uint64_t)(sbo >> 4) << 32) | ((uint64_t)mode << 62);
}

__device__ __forceinline__ void wgmma_ssp_n240_t01(float (&d)[120], uint64_t da, uint64_t db, int sd) {
  asm volatile("{\n.reg .pred p;\nsetp.ne.b32 p, %122, 0;\n"
    "wgmma.mma_async.sync.aligned.m64n240k16.f32.bf16.bf16 {%0, %1, %2, %3, %4, %5, %6, %7, %8, %9, %10, %11, %12, %13, %14, %15, %16, %17, %18, %19, %20, %21, %22, %23, %24, %25, %26, %27, %28, %29, %30, %31, %32, %33, %34, %35, %36, %37, %38, %39, %40, %41, %42, %43, %44, %45, %46, %47, %48, %49, %50, %51, %52, %53, %54, %55, %56, %57, %58, %59, %60, %61, %62, %63, %64, %65, %66, %67, %68, %69, %70, %71, %72, %73, %74, %75, %76, %77, %78, %79, %80, %81, %82, %83, %84, %85, %86, %87, %88, %89, %90, %91, %92, %93, %94, %95, %96, %97, %98, %99, %100, %101, %102, %103, %104, %105, %106, %107, %108, %109, %110, %111, %112, %113, %114, %115, %116, %117, %118, %119}, %120, %121, p, 1, 1, 0, 1;\n}\n"
    : "+f"(d[0]), "+f"(d[1]), "+f"(d[2]), "+f"(d[3]), "+f"(d[4]), "+f"(d[5]), "+f"(d[6]), "+f"(d[7]), "+f"(d[8]), "+f"(d[9]), "+f"(d[10]), "+f"(d[11]), "+f"(d[12]), "+f"(d[13]), "+f"(d[14]), "+f"(d[15]), "+f"(d[16]), "+f"(d[17]), "+f"(d[18]), "+f"(d[19]), "+f"(d[20]), "+f"(d[21]), "+f"(d[22]), "+f"(d[23]), "+f"(d[24]), "+f"(d[25]), "+f"(d[26]), "+f"(d[27]), "+f"(d[28]), "+f"(d[29]), "+f"(d[30]), "+f"(d[31]), "+f"(d[32]), "+f"(d[33]), "+f"(d[34]), "+f"(d[35]), "+f"(d[36]), "+f"(d[37]), "+f"(d[38]), "+f"(d[39]), "+f"(d[40]), "+f"(d[41]), "+f"(d[42]), "+f"(d[43]), "+f"(d[44]), "+f"(d[45]), "+f"(d[46]), "+f"(d[47]), "+f"(d[48]), "+f"(d[49]), "+f"(d[50]), "+f"(d[51]), "+f"(d[52]), "+f"(d[53]), "+f"(d[54]), "+f"(d[55]), "+f"(d[56]), "+f"(d[57]), "+f"(d[58]), "+f"(d[59]), "+f"(d[60]), "+f"(d[61]), "+f"(d[62]), "+f"(d[63]), "+f"(d[64]), "+f"(d[65]), "+f"(d[66]), "+f"(d[67]), "+f"(d[68]), "+f"(d[69]), "+f"(d[70]), "+f"(d[71]), "+f"(d[72]), "+f"(d[73]), "+f"(d[74]), "+f"(d[75]), "+f"(d[76]), "+f"(d[77]), "+f"(d[78]), "+f"(d[79]), "+f"(d[80]), "+f"(d[81]), "+f"(d[82]), "+f"(d[83]), "+f"(d[84]), "+f"(d[85]), "+f"(d[86]), "+f"(d[87]), "+f"(d[88]), "+f"(d[89]), "+f"(d[90]), "+f"(d[91]), "+f"(d[92]), "+f"(d[93]), "+f"(d[94]), "+f"(d[95]), "+f"(d[96]), "+f"(d[97]), "+f"(d[98]), "+f"(d[99]), "+f"(d[100]), "+f"(d[101]), "+f"(d[102]), "+f"(d[103]), "+f"(d[104]), "+f"(d[105]), "+f"(d[106]), "+f"(d[107]), "+f"(d[108]), "+f"(d[109]), "+f"(d[110]), "+f"(d[111]), "+f"(d[112]), "+f"(d[113]), "+f"(d[114]), "+f"(d[115]), "+f"(d[116]), "+f"(d[117]), "+f"(d[118]), "+f"(d[119])
    : "l"(da), "l"(db), "r"(sd));
}
__device__ __forceinline__ void wgmma_ssp_n216_t01(float (&d)[108], uint64_t da, uint64_t db, int sd) {
  asm volatile("{\n.reg .pred p;\nsetp.ne.b32 p, %110, 0;\n"
    "wgmma.mma_async.sync.aligned.m64n216k16.f32.bf16.bf16 {%0, %1, %2, %3, %4, %5, %6, %7, %8, %9, %10, %11, %12, %13, %14, %15, %16, %17, %18, %19, %20, %21, %22, %23, %24, %25, %26, %27, %28, %29, %30, %31, %32, %33, %34, %35, %36, %37, %38, %39, %40, %41, %42, %43, %44, %45, %46, %47, %48, %49, %50, %51, %52, %53, %54, %55, %56, %57, %58, %59, %60, %61, %62, %63, %64, %65, %66, %67, %68, %69, %70, %71, %72, %73, %74, %75, %76, %77, %78, %79, %80, %81, %82, %83, %84, %85, %86, %87, %88, %89, %90, %91, %92, %93, %94, %95, %96, %97, %98, %99, %100, %101, %102, %103, %104, %105, %106, %107}, %108, %109, p, 1, 1, 0, 1;\n}\n"
    : "+f"(d[0]), "+f"(d[1]), "+f"(d[2]), "+f"(d[3]), "+f"(d[4]), "+f"(d[5]), "+f"(d[6]), "+f"(d[7]), "+f"(d[8]), "+f"(d[9]), "+f"(d[10]), "+f"(d[11]), "+f"(d[12]), "+f"(d[13]), "+f"(d[14]), "+f"(d[15]), "+f"(d[16]), "+f"(d[17]), "+f"(d[18]), "+f"(d[19]), "+f"(d[20]), "+f"(d[21]), "+f"(d[22]), "+f"(d[23]), "+f"(d[24]), "+f"(d[25]), "+f"(d[26]), "+f"(d[27]), "+f"(d[28]), "+f"(d[29]), "+f"(d[30]), "+f"(d[31]), "+f"(d[32]), "+f"(d[33]), "+f"(d[34]), "+f"(d[35]), "+f"(d[36]), "+f"(d[37]), "+f"(d[38]), "+f"(d[39]), "+f"(d[40]), "+f"(d[41]), "+f"(d[42]), "+f"(d[43]), "+f"(d[44]), "+f"(d[45]), "+f"(d[46]), "+f"(d[47]), "+f"(d[48]), "+f"(d[49]), "+f"(d[50]), "+f"(d[51]), "+f"(d[52]), "+f"(d[53]), "+f"(d[54]), "+f"(d[55]), "+f"(d[56]), "+f"(d[57]), "+f"(d[58]), "+f"(d[59]), "+f"(d[60]), "+f"(d[61]), "+f"(d[62]), "+f"(d[63]), "+f"(d[64]), "+f"(d[65]), "+f"(d[66]), "+f"(d[67]), "+f"(d[68]), "+f"(d[69]), "+f"(d[70]), "+f"(d[71]), "+f"(d[72]), "+f"(d[73]), "+f"(d[74]), "+f"(d[75]), "+f"(d[76]), "+f"(d[77]), "+f"(d[78]), "+f"(d[79]), "+f"(d[80]), "+f"(d[81]), "+f"(d[82]), "+f"(d[83]), "+f"(d[84]), "+f"(d[85]), "+f"(d[86]), "+f"(d[87]), "+f"(d[88]), "+f"(d[89]), "+f"(d[90]), "+f"(d[91]), "+f"(d[92]), "+f"(d[93]), "+f"(d[94]), "+f"(d[95]), "+f"(d[96]), "+f"(d[97]), "+f"(d[98]), "+f"(d[99]), "+f"(d[100]), "+f"(d[101]), "+f"(d[102]), "+f"(d[103]), "+f"(d[104]), "+f"(d[105]), "+f"(d[106]), "+f"(d[107])
    : "l"(da), "l"(db), "r"(sd));
}
__device__ __forceinline__ void wgmma_ssp_n160_t01(float (&d)[80], uint64_t da, uint64_t db, int sd) {
  asm volatile("{\n.reg .pred p;\nsetp.ne.b32 p, %82, 0;\n"
    "wgmma.mma_async.sync.aligned.m64n160k16.f32.bf16.bf16 {%0, %1, %2, %3, %4, %5, %6, %7, %8, %9, %10, %11, %12, %13, %14, %15, %16, %17, %18, %19, %20, %21, %22, %23, %24, %25, %26, %27, %28, %29, %30, %31, %32, %33, %34, %35, %36, %37, %38, %39, %40, %41, %42, %43, %44, %45, %46, %47, %48, %49, %50, %51, %52, %53, %54, %55, %56, %57, %58, %59, %60, %61, %62, %63, %64, %65, %66, %67, %68, %69, %70, %71, %72, %73, %74, %75, %76, %77, %78, %79}, %80, %81, p, 1, 1, 0, 1;\n}\n"
    : "+f"(d[0]), "+f"(d[1]), "+f"(d[2]), "+f"(d[3]), "+f"(d[4]), "+f"(d[5]), "+f"(d[6]), "+f"(d[7]), "+f"(d[8]), "+f"(d[9]), "+f"(d[10]), "+f"(d[11]), "+f"(d[12]), "+f"(d[13]), "+f"(d[14]), "+f"(d[15]), "+f"(d[16]), "+f"(d[17]), "+f"(d[18]), "+f"(d[19]), "+f"(d[20]), "+f"(d[21]), "+f"(d[22]), "+f"(d[23]), "+f"(d[24]), "+f"(d[25]), "+f"(d[26]), "+f"(d[27]), "+f"(d[28]), "+f"(d[29]), "+f"(d[30]), "+f"(d[31]), "+f"(d[32]), "+f"(d[33]), "+f"(d[34]), "+f"(d[35]), "+f"(d[36]), "+f"(d[37]), "+f"(d[38]), "+f"(d[39]), "+f"(d[40]), "+f"(d[41]), "+f"(d[42]), "+f"(d[43]), "+f"(d[44]), "+f"(d[45]), "+f"(d[46]), "+f"(d[47]), "+f"(d[48]), "+f"(d[49]), "+f"(d[50]), "+f"(d[51]), "+f"(d[52]), "+f"(d[53]), "+f"(d[54]), "+f"(d[55]), "+f"(d[56]), "+f"(d[57]), "+f"(d[58]), "+f"(d[59]), "+f"(d[60]), "+f"(d[61]), "+f"(d[62]), "+f"(d[63]), "+f"(d[64]), "+f"(d[65]), "+f"(d[66]), "+f"(d[67]), "+f"(d[68]), "+f"(d[69]), "+f"(d[70]), "+f"(d[71]), "+f"(d[72]), "+f"(d[73]), "+f"(d[74]), "+f"(d[75]), "+f"(d[76]), "+f"(d[77]), "+f"(d[78]), "+f"(d[79])
    : "l"(da), "l"(db), "r"(sd));
}
__device__ __forceinline__ void wgmma_ss_n64_t00(float (&d)[32], uint64_t da, uint64_t db) {
  asm volatile("{\n.reg .pred p;\nsetp.ne.b32 p, 1, 0;\n"
    "wgmma.mma_async.sync.aligned.m64n64k16.f32.bf16.bf16 {%0, %1, %2, %3, %4, %5, %6, %7, %8, %9, %10, %11, %12, %13, %14, %15, %16, %17, %18, %19, %20, %21, %22, %23, %24, %25, %26, %27, %28, %29, %30, %31}, %32, %33, p, 1, 1, 0, 0;\n}\n"
    : "+f"(d[0]), "+f"(d[1]), "+f"(d[2]), "+f"(d[3]), "+f"(d[4]), "+f"(d[5]), "+f"(d[6]), "+f"(d[7]), "+f"(d[8]), "+f"(d[9]), "+f"(d[10]), "+f"(d[11]), "+f"(d[12]), "+f"(d[13]), "+f"(d[14]), "+f"(d[15]), "+f"(d[16]), "+f"(d[17]), "+f"(d[18]), "+f"(d[19]), "+f"(d[20]), "+f"(d[21]), "+f"(d[22]), "+f"(d[23]), "+f"(d[24]), "+f"(d[25]), "+f"(d[26]), "+f"(d[27]), "+f"(d[28]), "+f"(d[29]), "+f"(d[30]), "+f"(d[31])
    : "l"(da), "l"(db));
}
__device__ __forceinline__ void wgmma_ss0_n64_t00(float (&d)[32], uint64_t da, uint64_t db) {
  asm volatile("{\n.reg .pred p;\nsetp.ne.b32 p, 0, 0;\n"
    "wgmma.mma_async.sync.aligned.m64n64k16.f32.bf16.bf16 {%0, %1, %2, %3, %4, %5, %6, %7, %8, %9, %10, %11, %12, %13, %14, %15, %16, %17, %18, %19, %20, %21, %22, %23, %24, %25, %26, %27, %28, %29, %30, %31}, %32, %33, p, 1, 1, 0, 0;\n}\n"
    : "=f"(d[0]), "=f"(d[1]), "=f"(d[2]), "=f"(d[3]), "=f"(d[4]), "=f"(d[5]), "=f"(d[6]), "=f"(d[7]), "=f"(d[8]), "=f"(d[9]), "=f"(d[10]), "=f"(d[11]), "=f"(d[12]), "=f"(d[13]), "=f"(d[14]), "=f"(d[15]), "=f"(d[16]), "=f"(d[17]), "=f"(d[18]), "=f"(d[19]), "=f"(d[20]), "=f"(d[21]), "=f"(d[22]), "=f"(d[23]), "=f"(d[24]), "=f"(d[25]), "=f"(d[26]), "=f"(d[27]), "=f"(d[28]), "=f"(d[29]), "=f"(d[30]), "=f"(d[31])
    : "l"(da), "l"(db));
}
__device__ __forceinline__ void wgmma_rs_n24_t1(float (&d)[12], uint32_t a0, uint32_t a1, uint32_t a2, uint32_t a3, uint64_t db, int sd) {
  asm volatile("{\n.reg .pred p;\nsetp.ne.b32 p, %17, 0;\n"
    "wgmma.mma_async.sync.aligned.m64n24k16.f32.bf16.bf16 {%0, %1, %2, %3, %4, %5, %6, %7, %8, %9, %10, %11}, {%12, %13, %14, %15}, %16, p, 1, 1, 1;\n}\n"
    : "+f"(d[0]), "+f"(d[1]), "+f"(d[2]), "+f"(d[3]), "+f"(d[4]), "+f"(d[5]), "+f"(d[6]), "+f"(d[7]), "+f"(d[8]), "+f"(d[9]), "+f"(d[10]), "+f"(d[11])
    : "r"(a0), "r"(a1), "r"(a2), "r"(a3), "l"(db), "r"(sd));
}

constexpr int K1_NST = 4;
constexpr int NPROD = 2;
constexpr uint32_t PF0 = 128;
constexpr int K1_A_BYTES = 10 * 16384;
constexpr int K1_SMEM = K1_A_BYTES + K1_NST * 16384 + 1024 + 1024;

template <int BN, bool UNROLL, typename MMA, typename SIDE>
__device__ __forceinline__ void k1_mainloop(float (&acc)[BN / 2], MMA mma, SIDE side, uint32_t sA, uint32_t sB, uint32_t barA, uint32_t barF,
                                            uint32_t barE, uint32_t barE_peer, int it0, bool waitA, int wgi, bool elect) {
  const uint64_t dA0 = mk_desc(sA + wgi * 8192, 16, 1024, 1);
  const uint64_t dB0 = mk_desc(sB, 4096, 1024, 1);
  fence_regs(acc);
#pragma unroll(UNROLL ? 20 : 1)
  for (int s = 0; s < 20; s++) {
    const int it = it0 + s, st = it & (K1_NST - 1);
    if (waitA && !(s & 1)) mbar_wait(barA + 8 * (s >> 1), 0);
    mbar_wait(barF + 8 * st, (it / K1_NST) & 1);
    const uint64_t da = dA0 + (uint32_t)((s >> 1) * 1024 + (s & 1) * 4);
    const uint64_t db = dB0 + (uint32_t)(st * 1024);
    wg_fence();
    mma(acc, da, db, s);
    mma(acc, da + 2, db + 128, 1);
    wg_commit();
    side(s);
    if (s > 0) {
      wg_wait<1>();
      if (elect) { const int ps = (it - 1) & (K1_NST - 1); mbar_arrive_cluster(barE + 8 * ps); mbar_arrive_cluster(barE_peer + 8 * ps); }
    }
  }
  wg_wait<0>();
  fence_regs(acc);
  if (elect) { const int ps = (it0 + 19) & (K1_NST - 1); mbar_arrive_cluster(barE + 8 * ps); mbar_arrive_cluster(barE_peer + 8 * ps); }
}

__device__ __forceinline__ void st32(uint8_t* p, uint32_t v) { *reinterpret_cast<uint32_t*>(p) = v; }

__device__ __forceinline__ void k1_qkv_pack(const float (&acc)[120], uint32_t (&pk)[60], int slot0, int slab, int lane) {
  const bool lo2 = (lane & 3) < 2;
#pragma unroll
  for (int hp = 0; hp < 6; hp++) {
    const float sc0 = slot0 + 2 * hp < 32 ? 0.32259642f : 1.0f;
    float q[5][2];
#pragma unroll
    for (int jj = 0; jj < 5; jj++) {
      const int j = hp * 5 + jj;
      const float v0 = acc[4 * j] * sc0, v1 = acc[4 * j + 1] * sc0, v2 = acc[4 * j + 2] * sc0, v3 = acc[4 * j + 3] * sc0;
      pk[2 * j] = pack_bf16(v0, v1);
      pk[2 * j + 1] = pack_bf16(v2, v3);
      q[jj][0] = fmaf(v0, v0, v1 * v1);
      q[jj][1] = fmaf(v2, v2, v3 * v3);
    }
    uint32_t na = 0, nb = 0;
#pragma unroll
    for (int r = 0; r < 2; r++) {
      float a = q[0][r] + q[1][r] + (lo2 ? q[2][r] : 0.f), b = q[3][r] + q[4][r] + (lo2 ? 0.f : q[2][r]);
      a += __shfl_xor_sync(0xffffffffu, a, 1); b += __shfl_xor_sync(0xffffffffu, b, 1);
      a += __shfl_xor_sync(0xffffffffu, a, 2); b += __shfl_xor_sync(0xffffffffu, b, 2);
      na = max(na, __float_as_uint(a)); nb = max(nb, __float_as_uint(b));
    }
    na = __reduce_max_sync(0xffffffffu, na);
    nb = __reduce_max_sync(0xffffffffu, nb);
    if (lane < 2) g_norm[(slot0 + 2 * hp + lane) * 128 + slab] = __uint_as_float(lane ? nb : na);
  }
}
__device__ __forceinline__ void k1_qkv_store(const uint32_t (&pk)[60], int hp, int part, int slot0, int grp, int g, int t4) {
  const int slot = slot0 + 2 * hp, which = slot >> 5, head = slot & 31;
  const uint32_t gs = which == 0 ? 512u : 768u, hs = which == 0 ? 131072u : 196608u;
  uint8_t* p0 = g_QKV + (head * hs + grp * gs + g * 16 + (which == 0 ? 0u : (which == 1 ? KV_OFF : KV_OFF + 384u)));
  uint8_t* p1 = p0 + hs;
  const bool lo2 = t4 < 2;
  const int j = hp * 5;
  if (part == 0) {
    st32(p0 + t4 * 4, pk[2 * j]); st32(p0 + t4 * 4 + gs, pk[2 * j + 1]);
    st32(p0 + 128 + t4 * 4, pk[2 * j + 2]); st32(p0 + 128 + t4 * 4 + gs, pk[2 * j + 3]);
  } else if (part == 1) {
    uint8_t* pm = lo2 ? p0 + 256 + t4 * 4 : p1 + (t4 * 4 - 8);
    st32(pm, pk[2 * j + 4]); st32(pm + gs, pk[2 * j + 5]);
    uint8_t* pp = (t4 & 1) ? p1 : p0;
    if (lo2) {
      uint2 c0, c1;
      if (which == 0) { c0 = make_uint2(0x42FB47C0u, 0x0000BDCCu); c1 = c0; }
      else if (which == 1) {
        c0 = ((MUFU_MASK >> (grp & 15)) & 1) ? make_uint2(0u, 0u) : make_uint2(0x3F803F80u, 0x00003F80u);
        c1 = ((MUFU_MASK >> ((grp + 1) & 15)) & 1) ? make_uint2(0u, 0u) : make_uint2(0x3F803F80u, 0x00003F80u);
      } else { c0 = make_uint2(0x00003F80u, 0u); c1 = c0; }
      *reinterpret_cast<uint2*>(pp + 264) = c0;
      *reinterpret_cast<uint2*>(pp + 264 + gs) = c1;
    } else if (which == 0) {
      *reinterpret_cast<uint4*>(pp + 384) = make_uint4(0, 0, 0, 0);
      *reinterpret_cast<uint4*>(pp + 384 + 512) = make_uint4(0, 0, 0, 0);
    }
  } else {
    const uint32_t e2 = lo2 ? 8 + t4 * 4 : 120 + t4 * 4;
    st32(p1 + e2, pk[2 * j + 6]); st32(p1 + e2 + gs, pk[2 * j + 7]);
    st32(p1 + 128 + e2, pk[2 * j + 8]); st32(p1 + 128 + e2 + gs, pk[2 * j + 9]);
  }
}

__global__ void __cluster_dims__(2, 1, 1) __launch_bounds__(384, 1)
k1_proj(const __grid_constant__ CUtensorMap tmX, const __grid_constant__ CUtensorMap tmWqkv, const __grid_constant__ CUtensorMap tmW1,
        const __nv_bfloat16* __restrict__ b1, const __nv_bfloat16* __restrict__ gate_w, const uint8_t* __restrict__ x,
        const uint8_t* __restrict__ wqkv, const uint8_t* __restrict__ w1, const uint8_t* __restrict__ w2, const uint8_t* __restrict__ wo) {
  extern __shared__ uint8_t smem_raw[];
  const uint32_t sb = (smem_u32(smem_raw) + 1023u) & ~1023u;
  const uint32_t sA = sb, sB = sb + K1_A_BYTES, bars = sB + K1_NST * 16384;
  const uint32_t barA = bars, barF = bars + 80, barE = barF + 8 * K1_NST;
  const int tid = threadIdx.x, lane = tid & 31;
  const int warp = __shfl_sync(0xffffffffu, tid >> 5, 0);
  const int rb = blockIdx.x & 15, cg = blockIdx.x >> 4;
  const uint32_t rank = cluster_rank();
  if (tid == 0) {
    STAMP(0);
    prefetch_tmap(&tmX); prefetch_tmap(&tmWqkv); prefetch_tmap(&tmW1);
    for (int i = 0; i < 10; i++) mbar_init(barA + 8 * i, 1);
    for (int i = 0; i < K1_NST; i++) { mbar_init(barF + 8 * i, 1); mbar_init(barE + 8 * i, 16); }
    fence_barrier_init();
    fence_proxy_async();
    for (int i = 0; i < K1_NST; i++) {
      if (!(i & 1)) {
        mbar_expect_tx(barA + 4 * i, 16384);
        tma_2d(sA + (i >> 1) * 16384, &tmX, i * 32, rb * 128, barA + 4 * i);
      }
      mbar_expect_tx(barF + 8 * i, 16384);
      for (int b = 0; b < 4; b++) tma_2d(sB + i * 16384 + b * 4096, &tmWqkv, cg * 240 + b * 64, i * 32, barF + 8 * i);
    }
  }
  pdl_launch();
  __syncwarp();
  cluster_arrive_relaxed();
  cluster_wait();

  if (warp < 4) {
    asm volatile("setmaxnreg.dec.sync.aligned.u32 40;");
    if (warp == 0 || warp == 2) {
      if (lane == 0) {
        if (warp == 2) {
          for (int ka = 2; ka < 4; ka++) {
            mbar_expect_tx(barA + 8 * ka, 16384);
            tma_2d(sA + ka * 16384, &tmX, ka * 64, rb * 128, barA + 8 * ka);
          }
        }
#pragma unroll 1
        for (int it = K1_NST + (warp >> 1); it < 40; it += NPROD) {
          const int st = it & (K1_NST - 1);
          const bool t0 = it < 20;
          const CUtensorMap* m = t0 ? &tmWqkv : &tmW1;
          const int col = (t0 ? cg * 240 : cg * 216) + (int)rank * 128;
          const int k = (t0 ? it : it - 20) * 32;
          const uint32_t dst = sB + st * 16384 + rank * 8192;
          mbar_wait(barE + 8 * st, ((it / K1_NST) - 1) & 1);
          mbar_expect_tx(barF + 8 * st, 16384);
          tma_2d_mc(dst, m, col, k, barF + 8 * st, (uint16_t)3);
          tma_2d_mc(dst + 4096, m, col + 64, k, barF + 8 * st, (uint16_t)3);
          if (it < 10) {
            const int ka = it;
            mbar_expect_tx(barA + 8 * ka, 16384);
            tma_2d(sA + ka * 16384, &tmX, ka * 64, rb * 128, barA + 8 * ka);
          }
        }
      }
    } else if (warp == 3) {
      if (lane == 0) {
        const uint32_t b = blockIdx.x;
        l2_prefetch(wqkv + PF0 * 3840u + b * ((640u - PF0) * 30u), (640u - PF0) * 30u);
        mbar_wait(barA + 8 * 3, 0);
        l2_prefetch(w1 + b * 17280u, 17280u);
        mbar_wait(barA + 8 * 9, 0);
        l2_prefetch(w2 + b * 17280u, 17280u);
        l2_prefetch(wo + b * 6400u, 6400u);
      }
    } else if (warp == 1) {
      const int r = cg * 16 + (lane >> 1), half = lane & 1;
      float acc = 0.f;
      mbar_wait(barA + 72, 0);
#pragma unroll 1
      for (int kb = half * 5; kb < half * 5 + 5; kb++) {
        mbar_wait(barA + 8 * kb, 0);
#pragma unroll
        for (int c = 0; c < 8; c++) {
          uint4 xv;
          asm volatile("ld.shared.v4.u32 {%0,%1,%2,%3}, [%4];" : "=r"(xv.x), "=r"(xv.y), "=r"(xv.z), "=r"(xv.w)
                       : "r"(sA + kb * 16384 + r * 128 + ((c ^ (r & 7)) << 4)));
          const uint4 wv = __ldg(reinterpret_cast<const uint4*>(gate_w + kb * 64 + c * 8));
          acc = fmaf(bf_lo(xv.x), bf_lo(wv.x), acc); acc = fmaf(bf_hi(xv.x), bf_hi(wv.x), acc);
          acc = fmaf(bf_lo(xv.y), bf_lo(wv.y), acc); acc = fmaf(bf_hi(xv.y), bf_hi(wv.y), acc);
          acc = fmaf(bf_lo(xv.z), bf_lo(wv.z), acc); acc = fmaf(bf_hi(xv.z), bf_hi(wv.z), acc);
          acc = fmaf(bf_lo(xv.w), bf_lo(wv.w), acc); acc = fmaf(bf_hi(xv.w), bf_hi(wv.w), acc);
        }
      }
      acc += __shfl_xor_sync(0xffffffffu, acc, 1);
      if (!half) g_gate[rb * 128 + r] = 1.f / (1.f + __expf(-acc));
    }
  } else {
    const int wgi = (warp >> 2) - 1, wq = warp & 3, g = lane >> 2, t4 = lane & 3;
    const uint32_t barE_self = mapa(barE, rank), barE_peer = mapa(barE, rank ^ 1);
    const bool elect = lane == 0;
    asm volatile("setmaxnreg.inc.sync.aligned.u32 232;");
    uint32_t pk[60];
    const int grp = rb * 16 + wgi * 8 + wq * 2, slot0 = cg * 12;
    {
      float acc[120];
      k1_mainloop<240, false>(acc, [](float (&d)[120], uint64_t a, uint64_t b, int sd) { wgmma_ssp_n240_t01(d, a, b, sd); }, [](int) {},
                              sA, sB, barA, barF, barE_self, barE_peer, 0, true, wgi, elect);
      if (warp == 4) STAMP(1);
      k1_qkv_pack(acc, pk, slot0, rb * 8 + wgi * 4 + wq, lane);
    }
    if (warp == 4) STAMP(2);
    {
      float acc[108];
      k1_mainloop<216, true>(acc, [](float (&d)[108], uint64_t a, uint64_t b, int sd) { wgmma_ssp_n216_t01(d, a, b, sd); },
                             [&](int s) { if (s < 18) k1_qkv_store(pk, s / 3, s % 3, slot0, grp, g, t4); },
                             sA, sB, barA, barF, barE_self, barE_peer, 20, false, wgi, elect);
      if (warp == 8) STAMP(3);
      uint8_t* base = g_A2 + ((size_t)(rb * 296 + cg * 27) * 16 + wgi * 8 + wq * 2) * 128 + g * 16 + t4 * 4;
      const uint32_t* bp = reinterpret_cast<const uint32_t*>(b1 + cg * 216 + t4 * 2);
#pragma unroll
      for (int j = 0; j < 27; j++) {
        const uint32_t bv = __ldg(bp + j * 4);
        const float c0 = bf_lo(bv), c1 = bf_hi(bv);
        const float h0 = fmaxf(acc[4 * j] + c0, 0.f), h1 = fmaxf(acc[4 * j + 1] + c1, 0.f);
        const float h2 = fmaxf(acc[4 * j + 2] + c0, 0.f), h3 = fmaxf(acc[4 * j + 3] + c1, 0.f);
        st32(base + j * 2048, pack_bf16(h0 * h0, h1 * h1));
        st32(base + j * 2048 + 128, pack_bf16(h2 * h2, h3 * h3));
      }
    }
    if (warp == 8) STAMP(4);
  }
  __syncwarp();
  cluster_arrive_relaxed();
  cluster_wait();
}

constexpr int KV_HEAD_BYTES = 256 * 768, Q_BYTES = 8 * 4096;
constexpr int AT_NCHUNK = 16, AT_CHUNK_BYTES = KV_HEAD_BYTES / AT_NCHUNK;
constexpr int AT_SMEM = KV_HEAD_BYTES + Q_BYTES + 1024 + 1024;

template <int T0, int T1, int TOFF>
__device__ __forceinline__ void exp_tiles(const float (&s)[32], uint32_t (&p)[16], uint32_t cmask, uint32_t cone) {
#pragma unroll
  for (int t = T0; t < T1; t++) {
#pragma unroll
    for (int h = 0; h < 2; h++) {
      const float x0 = s[4 * t + 2 * h], x1 = s[4 * t + 2 * h + 1];
      uint32_t r;
      if ((MUFU_MASK >> ((t + TOFF) & 15)) & 1) {
        r = pack_bf16(ex2(x0), ex2(x1));
      } else {
        const uint32_t u = __byte_perm(__float_as_uint(x0), __float_as_uint(x1), 0x5410);
        uint32_t g;
        asm("lop3.b32 %0, %1, %2, %3, 0xEA;" : "=r"(g) : "r"(u), "r"(cmask), "r"(cone));
        r = hfma2_bf16(g, g, 0x40034003u) + u - g;
      }
      p[2 * t + h] = r;
      asm volatile("" : "+r"(p[2 * t + h])::"memory");
    }
  }
}
template <int TOFF>
__device__ __forceinline__ void exp_pv(const float (&s)[32], uint32_t (&p)[16], float (&o)[12], uint64_t dv, int sd, uint32_t cmask, uint32_t cone) {
  exp_tiles<0, 4, TOFF>(s, p, cmask, cone);
  wg_fence();
  wgmma_rs_n24_t1(o, p[0], p[1], p[2], p[3], dv, sd);
  wgmma_rs_n24_t1(o, p[4], p[5], p[6], p[7], dv + 96, 1);
  exp_tiles<4, 8, TOFF>(s, p, cmask, cone);
  wg_fence();
  wgmma_rs_n24_t1(o, p[8], p[9], p[10], p[11], dv + 192, 1);
  wgmma_rs_n24_t1(o, p[12], p[13], p[14], p[15], dv + 288, 1);
}
__device__ __forceinline__ void qk64(float (&s)[32], uint64_t dq, uint64_t dk) {
  wgmma_ss0_n64_t00(s, dq, dk);
  wgmma_ss_n64_t00(s, dq + 16, dk + 16);
}
__device__ __forceinline__ void attn_store(const float (&o)[12], int row0, int head, int lane) {
  const int t4 = lane & 3;
  const float l0 = __shfl_sync(0xffffffffu, o[8], (lane & ~3) | 2), l1 = __shfl_sync(0xffffffffu, o[10], (lane & ~3) | 2);
  const float r0 = __fdividef(g_gate[row0], l0), r1 = __fdividef(g_gate[row0 + 8], l1);
  uint8_t* base = g_A2 + ((size_t)((row0 >> 7) * 296 + 216) * 16 + ((row0 & 127) >> 3)) * 128 + (row0 & 7) * 16;
#pragma unroll
  for (int tt = 0; tt < 3; tt++) {
    const int d = tt * 8 + 2 * t4;
    if (d < 20) {
      const int col = head * 20 + d;
      uint8_t* ptr = base + (col >> 3) * 2048 + (col & 7) * 2;
      *reinterpret_cast<uint32_t*>(ptr) = pack_bf16(o[4 * tt] * r0, o[4 * tt + 1] * r0);
      *reinterpret_cast<uint32_t*>(ptr + 128) = pack_bf16(o[4 * tt + 2] * r1, o[4 * tt + 3] * r1);
    }
  }
}

__device__ __forceinline__ void attn_slow(uint32_t sb, uint32_t bb, int wg, int rowbase, int head, int lane) {
  const uint64_t dk0 = mk_desc(sb, 128, 768, 0), dv0 = mk_desc(sb + 384, 768, 128, 0);
  const uint64_t dq0 = mk_desc(sb + KV_HEAD_BYTES + wg * 8192, 128, 512, 0);
#pragma unroll 1
  for (int mt = 0; mt < 2; mt++) {
    float o[12], s[32];
    uint32_t p[16];
#pragma unroll
    for (int i = 0; i < 12; i++) o[i] = 0.f;
    float m0 = -INFINITY, m1 = -INFINITY;
#pragma unroll 1
    for (int b = 0; b < 32; b++) {
      if (mt == 0 && !(b & 1)) mbar_wait(bb + 8 * (b >> 1), 0);
      wg_fence();
      qk64(s, dq0 + (uint32_t)(mt * 256), dk0 + (uint32_t)(b * 384));
      wg_commit();
      wg_wait<0>();
      fence_regs(s);
      float n0 = m0, n1 = m1;
#pragma unroll
      for (int t = 0; t < 8; t++) { n0 = fmaxf(n0, fmaxf(s[4 * t], s[4 * t + 1])); n1 = fmaxf(n1, fmaxf(s[4 * t + 2], s[4 * t + 3])); }
      n0 = fmaxf(n0, __shfl_xor_sync(0xffffffffu, n0, 1)); n0 = fmaxf(n0, __shfl_xor_sync(0xffffffffu, n0, 2));
      n1 = fmaxf(n1, __shfl_xor_sync(0xffffffffu, n1, 1)); n1 = fmaxf(n1, __shfl_xor_sync(0xffffffffu, n1, 2));
      const float a0 = ex2(m0 - n0), a1 = ex2(m1 - n1);
      m0 = n0; m1 = n1;
#pragma unroll
      for (int t = 0; t < 3; t++) { o[4 * t] *= a0; o[4 * t + 1] *= a0; o[4 * t + 2] *= a1; o[4 * t + 3] *= a1; }
#pragma unroll
      for (int t = 0; t < 8; t++) {
        p[2 * t] = pack_bf16(ex2(s[4 * t] - m0), ex2(s[4 * t + 1] - m0));
        p[2 * t + 1] = pack_bf16(ex2(s[4 * t + 2] - m1), ex2(s[4 * t + 3] - m1));
      }
      fence_regs(o);
      wg_fence();
#pragma unroll
      for (int k = 0; k < 4; k++) wgmma_rs_n24_t1(o, p[4 * k], p[4 * k + 1], p[4 * k + 2], p[4 * k + 3], dv0 + (uint32_t)(b * 384 + k * 96), 1);
      wg_commit();
      wg_wait<0>();
      fence_regs(o);
    }
    attn_store(o, rowbase + mt * 64, head, lane);
  }
}

__global__ void __launch_bounds__(512, 1) k2_attn(int opaque_zero) {
  extern __shared__ uint8_t smem_raw[];
  const uint32_t sb = (smem_u32(smem_raw) + 1023u) & ~1023u;
  const uint32_t bb = sb + KV_HEAD_BYTES + Q_BYTES;
  const int tid = threadIdx.x, lane = tid & 31;
  const int warp = __shfl_sync(0xffffffffu, tid >> 5, 0), wg = warp >> 2;
  const int head = blockIdx.x >> 2, qb = blockIdx.x & 3;
  if (tid == 0) {
    STAMP(5);
    for (int i = 0; i <= AT_NCHUNK; i++) mbar_init(bb + 8 * i, 1);
    fence_barrier_init();
    fence_proxy_async();
  }
  pdl_launch();
  pdl_wait();
  if (tid == 0) {
    STAMP(6);
    mbar_expect_tx(bb + 8 * AT_NCHUNK, Q_BYTES);
    bulk_g2s(sb + KV_HEAD_BYTES, g_QKV + (size_t)blockIdx.x * Q_BYTES, Q_BYTES, bb + 8 * AT_NCHUNK);
    for (int i = 0; i < AT_NCHUNK; i++) {
      mbar_expect_tx(bb + 8 * i, AT_CHUNK_BYTES);
      bulk_g2s(sb + i * AT_CHUNK_BYTES, g_QKV + KV_OFF + (size_t)head * KV_HEAD_BYTES + i * AT_CHUNK_BYTES, AT_CHUNK_BYTES, bb + 8 * i);
    }
  }
  bool fast;
  {
    const uint32_t* nb = reinterpret_cast<const uint32_t*>(g_norm);
    const uint4 k4 = *reinterpret_cast<const uint4*>(nb + (32 + head) * 128 + lane * 4);
    const uint4 v4 = *reinterpret_cast<const uint4*>(nb + (64 + head) * 128 + lane * 4);
    const float nq = __uint_as_float(__reduce_max_sync(0xffffffffu, nb[head * 128 + qb * 32 + lane]));
    const float nk = __uint_as_float(__reduce_max_sync(0xffffffffu, max(max(k4.x, k4.y), max(k4.z, k4.w))));
    const float nv = __uint_as_float(__reduce_max_sync(0xffffffffu, max(max(v4.x, v4.y), max(v4.z, v4.w))));
    fast = (nq * nk <= 2304.0f) && (nq <= 1e30f) && (nk <= 1e30f) && (nv <= 1e30f) && (nv >= 1e-18f);
  }
  const int rowbase = qb * 512 + wg * 128 + (warp & 3) * 16 + (lane >> 2);
  __syncthreads();
  mbar_wait(bb + 8 * AT_NCHUNK, 0);
  if (!fast) {
    *reinterpret_cast<uint2*>(smem_raw + (sb - smem_u32(smem_raw)) + KV_HEAD_BYTES + (tid >> 3) * 512 + 256 + (tid & 7) * 16 + 8) = make_uint2(0u, 0u);
    fence_proxy_async();
    __syncthreads();
    attn_slow(sb, bb, wg, rowbase, head, lane);
    return;
  }
  uint32_t cmask = 0x007F007Fu + opaque_zero, cone = 0x3F803F80u + opaque_zero;
  const uint64_t dk0 = mk_desc(sb, 128, 768, 0), dv0 = mk_desc(sb + 384, 768, 128, 0);
  const uint64_t dq0 = mk_desc(sb + KV_HEAD_BYTES + wg * 8192, 128, 512, 0);
  float o[12], s0[32], s1[32];
  uint32_t p0[16], p1[16];
#pragma unroll
  for (int i = 0; i < 12; i++) o[i] = 0.f;
  fence_regs(o);
  mbar_wait(bb, 0);
  wg_fence();
  qk64(s0, dq0, dk0);
  wg_commit();
  wg_wait<0>();
  fence_regs(s0);
#pragma unroll 1
  for (int it = 0; it < 32; it++) {
    const int c = it & 15, mt = it >> 4;
    const uint64_t dq = dq0 + (uint32_t)(mt * 256);
    const uint32_t off = c * 768;
    wg_fence();
    qk64(s1, dq, dk0 + (off + 384));
    wg_commit();
    exp_pv<0>(s0, p0, o, dv0 + off, c, cmask, cone);
    wg_commit();
    wg_wait<1>();
    fence_regs(s1);
    const int cn = (c + 1) & 15;
    const uint64_t dqn = dq0 + (uint32_t)((((it + 1) >> 4) & 1) * 256);
    if (it < 15) mbar_wait(bb + 8 * cn, 0);
    wg_fence();
    qk64(s0, dqn, dk0 + (uint32_t)(cn * 768));
    wg_commit();
    exp_pv<8>(s1, p1, o, dv0 + (off + 384), 1, cmask, cone);
    wg_commit();
    wg_wait<0>();
    fence_regs(s0);
    fence_regs(o);
    if (c == 15) attn_store(o, rowbase + mt * 64, head, lane);
  }
  if (warp == 0) STAMP(8);
}

constexpr int K3_NST = 8, K3_STAGE = 8192 + 10240;
constexpr int K3_RED = 128 * 80 * 4;
constexpr int K3_SMEM = K3_NST * K3_STAGE + K3_RED + 1024 + 1024;

__global__ void __cluster_dims__(2, 1, 1) __launch_bounds__(288, 1)
k3_out(const __grid_constant__ CUtensorMap tmW2, const __grid_constant__ CUtensorMap tmWo, const __nv_bfloat16* __restrict__ b2,
       __nv_bfloat16* __restrict__ out) {
  extern __shared__ uint8_t smem_raw[];
  const uint32_t sb = (smem_u32(smem_raw) + 1023u) & ~1023u;
  const uint32_t sRed = sb + K3_NST * K3_STAGE, barF = sRed + K3_RED, barE = barF + 8 * K3_NST, barR = barE + 8 * K3_NST;
  const int tid = threadIdx.x, lane = tid & 31;
  const int warp = __shfl_sync(0xffffffffu, tid >> 5, 0);
  const uint32_t rank = cluster_rank();
  const int tile = blockIdx.x >> 1, rb = tile >> 2, ct = tile & 3;
  if (tid == 0) {
    STAMP(9);
    prefetch_tmap(&tmW2); prefetch_tmap(&tmWo);
    for (int i = 0; i < K3_NST; i++) { mbar_init(barF + 8 * i, 1); mbar_init(barE + 8 * i, 8); }
    mbar_init(barR, 1);
    fence_barrier_init();
    mbar_expect_tx(barR, K3_RED);
  }
  __syncwarp();
  cluster_arrive();
  cluster_wait();
  if (warp == 8) {
    if (lane == 0) {
      const int s0 = rank * 37;
      const uint8_t* asrc = g_A2 + (size_t)rb * 296 * 2048;
      for (int i = 0; i < K3_NST; i++) {
        const int s = s0 + i;
        mbar_expect_tx(barF + 8 * i, K3_STAGE);
        for (int b = 0; b < 5; b++) tma_2d(sb + i * K3_STAGE + 8192 + b * 2048, &tmW2, ct * 160 + b * 32, s * 32, barF + 8 * i);
      }
      pdl_wait();
      for (int i = 0; i < K3_NST; i++) bulk_g2s(sb + i * K3_STAGE, asrc + (size_t)(s0 + i) * 8192, 8192, barF + 8 * i);
#pragma unroll 1
      for (int i = K3_NST; i < 37; i++) {
        const int st = i & (K3_NST - 1), s = s0 + i;
        mbar_wait(barE + 8 * st, ((i / K3_NST) - 1) & 1);
        mbar_expect_tx(barF + 8 * st, K3_STAGE);
        bulk_g2s(sb + st * K3_STAGE, asrc + (size_t)s * 8192, 8192, barF + 8 * st);
        const CUtensorMap* m = s < 54 ? &tmW2 : &tmWo;
        const int k = (s < 54 ? s : s - 54) * 32;
        for (int b = 0; b < 5; b++) tma_2d(sb + st * K3_STAGE + 8192 + b * 2048, m, ct * 160 + b * 32, k, barF + 8 * st);
      }
    }
  } else {
    const int wgi = warp >> 2, wq = warp & 3, g = lane >> 2, t4 = lane & 3;
    const int rloc = wgi * 64 + wq * 16 + g, row = rb * 128 + rloc;
    const int col0 = ct * 160 + rank * 80 + t4 * 2;
    uint32_t bias[10];
#pragma unroll
    for (int j = 0; j < 10; j++) bias[j] = __ldg(reinterpret_cast<const uint32_t*>(b2 + col0 + j * 8));
    pdl_wait();
    if (warp == 0) STAMP(10);
    const float w0 = 1.f - g_gate[row], w1 = 1.f - g_gate[row + 8];
    float acc[80];
    const uint64_t dA0 = mk_desc(sb + wgi * 1024, 2048, 128, 0), dB0 = mk_desc(sb + 8192, 2048, 512, 2);
    const int nsw = rank ? 17 : 37;
    fence_regs(acc);
#pragma unroll 1
    for (int i = 0; i < 37; i++) {
      const int st = i & (K3_NST - 1);
      mbar_wait(barF + 8 * st, (i / K3_NST) & 1);
      const uint32_t off = st * (K3_STAGE >> 4);
      wg_fence();
      wgmma_ssp_n160_t01(acc, dA0 + off, dB0 + off, i);
      wgmma_ssp_n160_t01(acc, dA0 + off + 256, dB0 + off + 64, 1);
      wg_commit();
      if (i + 1 == nsw) {
        wg_wait<0>();
        fence_regs(acc);
#pragma unroll
        for (int j = 0; j < 20; j++) { acc[4 * j] *= w0; acc[4 * j + 1] *= w0; acc[4 * j + 2] *= w1; acc[4 * j + 3] *= w1; }
        fence_regs(acc);
      } else {
        wg_wait<1>();
      }
      if (i > 0 && lane == 0) mbar_arrive(barE + 8 * ((i - 1) & (K3_NST - 1)));
    }
    wg_wait<0>();
    fence_regs(acc);
    if (warp == 0) STAMP(11);
    const uint32_t peerRed = mapa(sRed, rank ^ 1) + tid * 16, peerBar = mapa(barR, rank ^ 1);
#pragma unroll
    for (int j = 0; j < 10; j++) {
      const float a0 = rank ? acc[4 * j] : acc[40 + 4 * j], a1 = rank ? acc[4 * j + 1] : acc[40 + 4 * j + 1];
      const float a2 = rank ? acc[4 * j + 2] : acc[40 + 4 * j + 2], a3 = rank ? acc[4 * j + 3] : acc[40 + 4 * j + 3];
      asm volatile("st.async.weak.shared::cluster.mbarrier::complete_tx::bytes.v4.f32 [%0], {%1, %2, %3, %4}, [%5];"
                   ::"r"(peerRed + j * 4096), "f"(a0), "f"(a1), "f"(a2), "f"(a3), "r"(peerBar) : "memory");
    }
    mbar_wait(barR, 0);
    if (warp == 0) STAMP(13);
#pragma unroll
    for (int j = 0; j < 10; j++) {
      float p0, p1, p2, p3;
      asm volatile("ld.shared.v4.f32 {%0, %1, %2, %3}, [%4];" : "=f"(p0), "=f"(p1), "=f"(p2), "=f"(p3) : "r"(sRed + tid * 16 + j * 4096));
      const float a0 = rank ? acc[40 + 4 * j] : acc[4 * j], a1 = rank ? acc[40 + 4 * j + 1] : acc[4 * j + 1];
      const float a2 = rank ? acc[40 + 4 * j + 2] : acc[4 * j + 2], a3 = rank ? acc[40 + 4 * j + 3] : acc[4 * j + 3];
      const float c0 = bf_lo(bias[j]), c1 = bf_hi(bias[j]);
      *reinterpret_cast<uint32_t*>(out + (size_t)row * D_ + col0 + j * 8) = pack_bf16(fmaf(w0, c0, a0 + p0), fmaf(w0, c1, a1 + p1));
      *reinterpret_cast<uint32_t*>(out + (size_t)(row + 8) * D_ + col0 + j * 8) = pack_bf16(fmaf(w1, c0, a2 + p2), fmaf(w1, c1, a3 + p3));
    }
    if (warp == 0) STAMP(12);
  }
}

typedef CUresult (*EncodeFn)(CUtensorMap*, CUtensorMapDataType, cuuint32_t, void*, const cuuint64_t*, const cuuint64_t*, const cuuint32_t*,
                             const cuuint32_t*, CUtensorMapInterleave, CUtensorMapSwizzle, CUtensorMapL2promotion, CUtensorMapFloatOOBfill);

void make_map(EncodeFn fn, CUtensorMap* m, const void* ptr, uint64_t inner, uint64_t outer, uint32_t box_inner, uint32_t box_outer, CUtensorMapSwizzle sw) {
  cuuint64_t dims[2] = {inner, outer};
  cuuint64_t strides[1] = {inner * 2};
  cuuint32_t box[2] = {box_inner, box_outer};
  cuuint32_t es[2] = {1, 1};
  fn(m, CU_TENSOR_MAP_DATA_TYPE_BFLOAT16, 2, const_cast<void*>(ptr), dims, strides, box, es, CU_TENSOR_MAP_INTERLEAVE_NONE, sw,
     CU_TENSOR_MAP_L2_PROMOTION_L2_256B, CU_TENSOR_MAP_FLOAT_OOB_FILL_NONE);
}

}

extern "C" void kernel_launch(void* const* d_in, const int* in_sizes, int n_in, void* d_out, int out_size) {
  (void)in_sizes; (void)n_in; (void)out_size;
  const __nv_bfloat16* x = (const __nv_bfloat16*)d_in[0];
  const __nv_bfloat16* wqkv = (const __nv_bfloat16*)d_in[1];
  const __nv_bfloat16* wo = (const __nv_bfloat16*)d_in[2];
  const __nv_bfloat16* w1 = (const __nv_bfloat16*)d_in[4];
  const __nv_bfloat16* b1 = (const __nv_bfloat16*)d_in[5];
  const __nv_bfloat16* w2 = (const __nv_bfloat16*)d_in[6];
  const __nv_bfloat16* b2 = (const __nv_bfloat16*)d_in[7];
  const __nv_bfloat16* gw = (const __nv_bfloat16*)d_in[8];

  static EncodeFn enc = nullptr;
  if (!enc) {
    void* p = nullptr;
    cudaDriverEntryPointQueryResult qr;
    cudaGetDriverEntryPoint("cuTensorMapEncodeTiled", &p, cudaEnableDefault, &qr);
    enc = (EncodeFn)p;
    cudaFuncSetAttribute(k1_proj, cudaFuncAttributeMaxDynamicSharedMemorySize, K1_SMEM);
    cudaFuncSetAttribute(k2_attn, cudaFuncAttributeMaxDynamicSharedMemorySize, AT_SMEM);
    cudaFuncSetAttribute(k3_out, cudaFuncAttributeMaxDynamicSharedMemorySize, K3_SMEM);
  }
  CUtensorMap tmX, tmWqkv, tmW1, tmW2, tmWo;
  make_map(enc, &tmX, x, D_, S_, 64, 128, CU_TENSOR_MAP_SWIZZLE_128B);
  make_map(enc, &tmWqkv, wqkv, 3 * D_, D_, 64, 32, CU_TENSOR_MAP_SWIZZLE_128B);
  make_map(enc, &tmW1, w1, F_, D_, 64, 32, CU_TENSOR_MAP_SWIZZLE_128B);
  make_map(enc, &tmW2, w2, D_, F_, 32, 32, CU_TENSOR_MAP_SWIZZLE_64B);
  make_map(enc, &tmWo, wo, D_, D_, 32, 32, CU_TENSOR_MAP_SWIZZLE_64B);

  cudaStream_t st = cudaStreamPerThread;
  k1_proj<<<128, 384, K1_SMEM, st>>>(tmX, tmWqkv, tmW1, b1, gw, (const uint8_t*)x, (const uint8_t*)wqkv, (const uint8_t*)w1,
                                     (const uint8_t*)w2, (const uint8_t*)wo);

  cudaLaunchAttribute at[1];
  at[0].id = cudaLaunchAttributeProgrammaticStreamSerialization;
  at[0].val.programmaticStreamSerializationAllowed = 1;
  {
    cudaLaunchConfig_t cfg = {};
    cfg.gridDim = dim3(128); cfg.blockDim = dim3(512); cfg.dynamicSmemBytes = AT_SMEM; cfg.stream = st;
    cfg.attrs = at; cfg.numAttrs = 1;
    cudaLaunchKernelEx(&cfg, k2_attn, 0);
  }
  {
    cudaLaunchConfig_t cfg = {};
    cfg.gridDim = dim3(128); cfg.blockDim = dim3(288); cfg.dynamicSmemBytes = K3_SMEM; cfg.stream = st;
    cfg.attrs = at; cfg.numAttrs = 1;
    cudaLaunchKernelEx(&cfg, k3_out, tmW2, tmWo, b2, (__nv_bfloat16*)d_out);
  }
}
```

```cpp
#include <cuda_runtime.h>
#include <cuda_bf16.h>
#include <cuda.h>
#include <stdint.h>

namespace {

constexpr int S_ = 2048, D_ = 640, NH = 32, F_ = 1728;

constexpr uint32_t KV_OFF = NH * 256 * 512;
__device__ __align__(1024) uint8_t g_QKV[NH * 256 * 512 + NH * 256 * 768];
__device__ __align__(1024) uint8_t g_A2[16 * 296 * 2048];
__device__ float g_gate[S_];
__device__ __align__(16) float g_norm[96 * 128];

constexpr uint32_t MUFU_MASK = 0x5151u;

#define STAMP(i) do { } while (0)

__device__ __forceinline__ uint32_t smem_u32(const void* p) { return (uint32_t)__cvta_generic_to_shared(p); }
__device__ __forceinline__ void wg_fence() { asm volatile("wgmma.fence.sync.aligned;" ::: "memory"); }
__device__ __forceinline__ void wg_commit() { asm volatile("wgmma.commit_group.sync.aligned;" ::: "memory"); }
template <int N> __device__ __forceinline__ void wg_wait() { asm volatile("wgmma.wait_group.sync.aligned %0;" ::"n"(N) : "memory"); }
template <int N> __device__ __forceinline__ void fence_regs(float (&r)[N]) {
#pragma unroll
  for (int i = 0; i < N; i++) asm volatile("" : "+f"(r[i])::"memory");
}
__device__ __forceinline__ float ex2(float x) { float y; asm("ex2.approx.ftz.f32 %0, %1;" : "=f"(y) : "f"(x)); return y; }
__device__ __forceinline__ uint32_t pack_bf16(float lo, float hi) { uint32_t y; asm("cvt.rn.bf16x2.f32 %0, %1, %2;" : "=r"(y) : "f"(hi), "f"(lo)); return y; }
__device__ __forceinline__ uint32_t hfma2_bf16(uint32_t a, uint32_t b, uint32_t c) { uint32_t y; asm("fma.rn.bf16x2 %0, %1, %2, %3;" : "=r"(y) : "r"(a), "r"(b), "r"(c)); return y; }
__device__ __forceinline__ float bf_lo(uint32_t v) { return __uint_as_float(v << 16); }
__device__ __forceinline__ float bf_hi(uint32_t v) { return __uint_as_float(v & 0xffff0000u); }
__device__ __forceinline__ void mbar_init(uint32_t bar, int cnt) { asm volatile("mbarrier.init.shared::cta.b64 [%0], %1;" ::"r"(bar), "r"(cnt)); }
__device__ __forceinline__ void mbar_expect_tx(uint32_t bar, uint32_t bytes) { asm volatile("mbarrier.arrive.expect_tx.shared::cta.b64 _, [%0], %1;" ::"r"(bar), "r"(bytes) : "memory"); }
__device__ __forceinline__ void mbar_arrive(uint32_t bar) { asm volatile("mbarrier.arrive.shared::cta.b64 _, [%0];" ::"r"(bar) : "memory"); }
__device__ __forceinline__ void mbar_arrive_cluster(uint32_t cluster_addr) { asm volatile("mbarrier.arrive.shared::cluster.b64 _, [%0];" ::"r"(cluster_addr) : "memory"); }
__device__ __forceinline__ void mbar_wait(uint32_t bar, uint32_t parity) {
  asm volatile(
      "{\n.reg .pred p;\n.reg .u32 n;\n"
      "mbarrier.try_wait.parity.shared::cta.b64 p, [%0], %1;\n"
      "@p bra DONE;\n"
      "mov.u32 n, 0;\n"
      "LOOP:\n"
      "mbarrier.try_wait.parity.shared::cta.b64 p, [%0], %1;\n"
      "@p bra DONE;\n"
      "add.u32 n, n, 1;\n"
      "setp.lt.u32 p, n, 0x1000000;\n"
      "@p bra LOOP;\n"
      "trap;\n"
      "DONE:\n}\n" ::"r"(bar), "r"(parity) : "memory");
}
__device__ __forceinline__ void bulk_g2s(uint32_t dst, const void* src, uint32_t bytes, uint32_t bar) {
  asm volatile("cp.async.bulk.shared::cluster.global.mbarrier::complete_tx::bytes [%0], [%1], %2, [%3];" ::"r"(dst), "l"(src), "r"(bytes), "r"(bar) : "memory");
}
__device__ __forceinline__ void l2_prefetch(const void* src, uint32_t bytes) {
  asm volatile("cp.async.bulk.prefetch.L2.global [%0], %1;" ::"l"(src), "r"(bytes) : "memory");
}
__device__ __forceinline__ void tma_2d(uint32_t dst, const CUtensorMap* m, int c0, int c1, uint32_t bar) {
  asm volatile("cp.async.bulk.tensor.2d.shared::cluster.global.mbarrier::complete_tx::bytes [%0], [%1, {%3, %4}], [%2];" ::"r"(dst), "l"(m), "r"(bar), "r"(c0), "r"(c1) : "memory");
}
__device__ __forceinline__ void tma_2d_mc(uint32_t dst, const CUtensorMap* m, int c0, int c1, uint32_t bar, uint16_t mask) {
  asm volatile("cp.async.bulk.tensor.2d.shared::cluster.global.mbarrier::complete_tx::bytes.multicast::cluster [%0], [%1, {%3, %4}], [%2], %5;" ::"r"(dst), "l"(m), "r"(bar), "r"(c0), "r"(c1), "h"(mask) : "memory");
}
__device__ __forceinline__ uint32_t mapa(uint32_t addr, uint32_t rank) { uint32_t r; asm("mapa.shared::cluster.u32 %0, %1, %2;" : "=r"(r) : "r"(addr), "r"(rank)); return r; }
__device__ __forceinline__ uint32_t cluster_rank() { uint32_t r; asm("mov.u32 %0, %%cluster_ctarank;" : "=r"(r)); return r; }
__device__ __forceinline__ void cluster_arrive() { asm volatile("barrier.cluster.arrive.release.aligned;" ::: "memory"); }
__device__ __forceinline__ void cluster_arrive_relaxed() { asm volatile("barrier.cluster.arrive.relaxed.aligned;" ::: "memory"); }
__device__ __forceinline__ void cluster_wait() { asm volatile("barrier.cluster.wait.acquire.aligned;" ::: "memory"); }
__device__ __forceinline__ void bar_sync(int id, int n) { asm volatile("bar.sync %0, %1;" ::"r"(id), "r"(n) : "memory"); }
__device__ __forceinline__ void bar_arrive(int id, int n) { asm volatile("bar.arrive %0, %1;" ::"r"(id), "r"(n) : "memory"); }
__device__ __forceinline__ void pdl_launch() { asm volatile("griddepcontrol.launch_dependents;" ::: "memory"); }
__device__ __forceinline__ void pdl_wait() { asm volatile("griddepcontrol.wait;" ::: "memory"); }
__device__ __forceinline__ void fence_barrier_init() { asm volatile("fence.mbarrier_init.release.cluster;" ::: "memory"); }
__device__ __forceinline__ void fence_proxy_async() { asm volatile("fence.proxy.async.shared::cta;" ::: "memory"); }
__device__ __forceinline__ void prefetch_tmap(const CUtensorMap* m) { asm volatile("prefetch.tensormap [%0];" ::"l"(m) : "memory"); }
__device__ __forceinline__ uint64_t mk_desc(uint32_t addr, uint32_t lbo, uint32_t sbo, uint32_t mode) {
  return (uint64_t)((addr & 0x3FFFF) >> 4) | ((uint64_t)(lbo >> 4) << 16) | ((uint64_t)(sbo >> 4) << 32) | ((uint64_t)mode << 62);
}

__device__ __forceinline__ void wgmma_ssp_n240_t01(float (&d)[120], uint64_t da, uint64_t db, int sd) {
  asm volatile("{\n.reg .pred p;\nsetp.ne.b32 p, %122, 0;\n"
    "wgmma.mma_async.sync.aligned.m64n240k16.f32.bf16.bf16 {%0, %1, %2, %3, %4, %5, %6, %7, %8, %9, %10, %11, %12, %13, %14, %15, %16, %17, %18, %19, %20, %21, %22, %23, %24, %25, %26, %27, %28, %29, %30, %31, %32, %33, %34, %35, %36, %37, %38, %39, %40, %41, %42, %43, %44, %45, %46, %47, %48, %49, %50, %51, %52, %53, %54, %55, %56, %57, %58, %59, %60, %61, %62, %63, %64, %65, %66, %67, %68, %69, %70, %71, %72, %73, %74, %75, %76, %77, %78, %79, %80, %81, %82, %83, %84, %85, %86, %87, %88, %89, %90, %91, %92, %93, %94, %95, %96, %97, %98, %99, %100, %101, %102, %103, %104, %105, %106, %107, %108, %109, %110, %111, %112, %113, %114, %115, %116, %117, %118, %119}, %120, %121, p, 1, 1, 0, 1;\n}\n"
    : "+f"(d[0]), "+f"(d[1]), "+f"(d[2]), "+f"(d[3]), "+f"(d[4]), "+f"(d[5]), "+f"(d[6]), "+f"(d[7]), "+f"(d[8]), "+f"(d[9]), "+f"(d[10]), "+f"(d[11]), "+f"(d[12]), "+f"(d[13]), "+f"(d[14]), "+f"(d[15]), "+f"(d[16]), "+f"(d[17]), "+f"(d[18]), "+f"(d[19]), "+f"(d[20]), "+f"(d[21]), "+f"(d[22]), "+f"(d[23]), "+f"(d[24]), "+f"(d[25]), "+f"(d[26]), "+f"(d[27]), "+f"(d[28]), "+f"(d[29]), "+f"(d[30]), "+f"(d[31]), "+f"(d[32]), "+f"(d[33]), "+f"(d[34]), "+f"(d[35]), "+f"(d[36]), "+f"(d[37]), "+f"(d[38]), "+f"(d[39]), "+f"(d[40]), "+f"(d[41]), "+f"(d[42]), "+f"(d[43]), "+f"(d[44]), "+f"(d[45]), "+f"(d[46]), "+f"(d[47]), "+f"(d[48]), "+f"(d[49]), "+f"(d[50]), "+f"(d[51]), "+f"(d[52]), "+f"(d[53]), "+f"(d[54]), "+f"(d[55]), "+f"(d[56]), "+f"(d[57]), "+f"(d[58]), "+f"(d[59]), "+f"(d[60]), "+f"(d[61]), "+f"(d[62]), "+f"(d[63]), "+f"(d[64]), "+f"(d[65]), "+f"(d[66]), "+f"(d[67]), "+f"(d[68]), "+f"(d[69]), "+f"(d[70]), "+f"(d[71]), "+f"(d[72]), "+f"(d[73]), "+f"(d[74]), "+f"(d[75]), "+f"(d[76]), "+f"(d[77]), "+f"(d[78]), "+f"(d[79]), "+f"(d[80]), "+f"(d[81]), "+f"(d[82]), "+f"(d[83]), "+f"(d[84]), "+f"(d[85]), "+f"(d[86]), "+f"(d[87]), "+f"(d[88]), "+f"(d[89]), "+f"(d[90]), "+f"(d[91]), "+f"(d[92]), "+f"(d[93]), "+f"(d[94]), "+f"(d[95]), "+f"(d[96]), "+f"(d[97]), "+f"(d[98]), "+f"(d[99]), "+f"(d[100]), "+f"(d[101]), "+f"(d[102]), "+f"(d[103]), "+f"(d[104]), "+f"(d[105]), "+f"(d[106]), "+f"(d[107]), "+f"(d[108]), "+f"(d[109]), "+f"(d[110]), "+f"(d[111]), "+f"(d[112]), "+f"(d[113]), "+f"(d[114]), "+f"(d[115]), "+f"(d[116]), "+f"(d[117]), "+f"(d[118]), "+f"(d[119])
    : "l"(da), "l"(db), "r"(sd));
}
__device__ __forceinline__ void wgmma_ssp_n216_t01(float (&d)[108], uint64_t da, uint64_t db, int sd) {
  asm volatile("{\n.reg .pred p;\nsetp.ne.b32 p, %110, 0;\n"
    "wgmma.mma_async.sync.aligned.m64n216k16.f32.bf16.bf16 {%0, %1, %2, %3, %4, %5, %6, %7, %8, %9, %10, %11, %12, %13, %14, %15, %16, %17, %18, %19, %20, %21, %22, %23, %24, %25, %26, %27, %28, %29, %30, %31, %32, %33, %34, %35, %36, %37, %38, %39, %40, %41, %42, %43, %44, %45, %46, %47, %48, %49, %50, %51, %52, %53, %54, %55, %56, %57, %58, %59, %60, %61, %62, %63, %64, %65, %66, %67, %68, %69, %70, %71, %72, %73, %74, %75, %76, %77, %78, %79, %80, %81, %82, %83, %84, %85, %86, %87, %88, %89, %90, %91, %92, %93, %94, %95, %96, %97, %98, %99, %100, %101, %102, %103, %104, %105, %106, %107}, %108, %109, p, 1, 1, 0, 1;\n}\n"
    : "+f"(d[0]), "+f"(d[1]), "+f"(d[2]), "+f"(d[3]), "+f"(d[4]), "+f"(d[5]), "+f"(d[6]), "+f"(d[7]), "+f"(d[8]), "+f"(d[9]), "+f"(d[10]), "+f"(d[11]), "+f"(d[12]), "+f"(d[13]), "+f"(d[14]), "+f"(d[15]), "+f"(d[16]), "+f"(d[17]), "+f"(d[18]), "+f"(d[19]), "+f"(d[20]), "+f"(d[21]), "+f"(d[22]), "+f"(d[23]), "+f"(d[24]), "+f"(d[25]), "+f"(d[26]), "+f"(d[27]), "+f"(d[28]), "+f"(d[29]), "+f"(d[30]), "+f"(d[31]), "+f"(d[32]), "+f"(d[33]), "+f"(d[34]), "+f"(d[35]), "+f"(d[36]), "+f"(d[37]), "+f"(d[38]), "+f"(d[39]), "+f"(d[40]), "+f"(d[41]), "+f"(d[42]), "+f"(d[43]), "+f"(d[44]), "+f"(d[45]), "+f"(d[46]), "+f"(d[47]), "+f"(d[48]), "+f"(d[49]), "+f"(d[50]), "+f"(d[51]), "+f"(d[52]), "+f"(d[53]), "+f"(d[54]), "+f"(d[55]), "+f"(d[56]), "+f"(d[57]), "+f"(d[58]), "+f"(d[59]), "+f"(d[60]), "+f"(d[61]), "+f"(d[62]), "+f"(d[63]), "+f"(d[64]), "+f"(d[65]), "+f"(d[66]), "+f"(d[67]), "+f"(d[68]), "+f"(d[69]), "+f"(d[70]), "+f"(d[71]), "+f"(d[72]), "+f"(d[73]), "+f"(d[74]), "+f"(d[75]), "+f"(d[76]), "+f"(d[77]), "+f"(d[78]), "+f"(d[79]), "+f"(d[80]), "+f"(d[81]), "+f"(d[82]), "+f"(d[83]), "+f"(d[84]), "+f"(d[85]), "+f"(d[86]), "+f"(d[87]), "+f"(d[88]), "+f"(d[89]), "+f"(d[90]), "+f"(d[91]), "+f"(d[92]), "+f"(d[93]), "+f"(d[94]), "+f"(d[95]), "+f"(d[96]), "+f"(d[97]), "+f"(d[98]), "+f"(d[99]), "+f"(d[100]), "+f"(d[101]), "+f"(d[102]), "+f"(d[103]), "+f"(d[104]), "+f"(d[105]), "+f"(d[106]), "+f"(d[107])
    : "l"(da), "l"(db), "r"(sd));
}
__device__ __forceinline__ void wgmma_ssp_n160_t01(float (&d)[80], uint64_t da, uint64_t db, int sd) {
  asm volatile("{\n.reg .pred p;\nsetp.ne.b32 p, %82, 0;\n"
    "wgmma.mma_async.sync.aligned.m64n160k16.f32.bf16.bf16 {%0, %1, %2, %3, %4, %5, %6, %7, %8, %9, %10, %11, %12, %13, %14, %15, %16, %17, %18, %19, %20, %21, %22, %23, %24, %25, %26, %27, %28, %29, %30, %31, %32, %33, %34, %35, %36, %37, %38, %39, %40, %41, %42, %43, %44, %45, %46, %47, %48, %49, %50, %51, %52, %53, %54, %55, %56, %57, %58, %59, %60, %61, %62, %63, %64, %65, %66, %67, %68, %69, %70, %71, %72, %73, %74, %75, %76, %77, %78, %79}, %80, %81, p, 1, 1, 0, 1;\n}\n"
    : "+f"(d[0]), "+f"(d[1]), "+f"(d[2]), "+f"(d[3]), "+f"(d[4]), "+f"(d[5]), "+f"(d[6]), "+f"(d[7]), "+f"(d[8]), "+f"(d[9]), "+f"(d[10]), "+f"(d[11]), "+f"(d[12]), "+f"(d[13]), "+f"(d[14]), "+f"(d[15]), "+f"(d[16]), "+f"(d[17]), "+f"(d[18]), "+f"(d[19]), "+f"(d[20]), "+f"(d[21]), "+f"(d[22]), "+f"(d[23]), "+f"(d[24]), "+f"(d[25]), "+f"(d[26]), "+f"(d[27]), "+f"(d[28]), "+f"(d[29]), "+f"(d[30]), "+f"(d[31]), "+f"(d[32]), "+f"(d[33]), "+f"(d[34]), "+f"(d[35]), "+f"(d[36]), "+f"(d[37]), "+f"(d[38]), "+f"(d[39]), "+f"(d[40]), "+f"(d[41]), "+f"(d[42]), "+f"(d[43]), "+f"(d[44]), "+f"(d[45]), "+f"(d[46]), "+f"(d[47]), "+f"(d[48]), "+f"(d[49]), "+f"(d[50]), "+f"(d[51]), "+f"(d[52]), "+f"(d[53]), "+f"(d[54]), "+f"(d[55]), "+f"(d[56]), "+f"(d[57]), "+f"(d[58]), "+f"(d[59]), "+f"(d[60]), "+f"(d[61]), "+f"(d[62]), "+f"(d[63]), "+f"(d[64]), "+f"(d[65]), "+f"(d[66]), "+f"(d[67]), "+f"(d[68]), "+f"(d[69]), "+f"(d[70]), "+f"(d[71]), "+f"(d[72]), "+f"(d[73]), "+f"(d[74]), "+f"(d[75]), "+f"(d[76]), "+f"(d[77]), "+f"(d[78]), "+f"(d[79])
    : "l"(da), "l"(db), "r"(sd));
}
__device__ __forceinline__ void wgmma_ss_n64_t00(float (&d)[32], uint64_t da, uint64_t db) {
  asm volatile("{\n.reg .pred p;\nsetp.ne.b32 p, 1, 0;\n"
    "wgmma.mma_async.sync.aligned.m64n64k16.f32.bf16.bf16 {%0, %1, %2, %3, %4, %5, %6, %7, %8, %9, %10, %11, %12, %13, %14, %15, %16, %17, %18, %19, %20, %21, %22, %23, %24, %25, %26, %27, %28, %29, %30, %31}, %32, %33, p, 1, 1, 0, 0;\n}\n"
    : "+f"(d[0]), "+f"(d[1]), "+f"(d[2]), "+f"(d[3]), "+f"(d[4]), "+f"(d[5]), "+f"(d[6]), "+f"(d[7]), "+f"(d[8]), "+f"(d[9]), "+f"(d[10]), "+f"(d[11]), "+f"(d[12]), "+f"(d[13]), "+f"(d[14]), "+f"(d[15]), "+f"(d[16]), "+f"(d[17]), "+f"(d[18]), "+f"(d[19]), "+f"(d[20]), "+f"(d[21]), "+f"(d[22]), "+f"(d[23]), "+f"(d[24]), "+f"(d[25]), "+f"(d[26]), "+f"(d[27]), "+f"(d[28]), "+f"(d[29]), "+f"(d[30]), "+f"(d[31])
    : "l"(da), "l"(db));
}
__device__ __forceinline__ void wgmma_ss0_n64_t00(float (&d)[32], uint64_t da, uint64_t db) {
  asm volatile("{\n.reg .pred p;\nsetp.ne.b32 p, 0, 0;\n"
    "wgmma.mma_async.sync.aligned.m64n64k16.f32.bf16.bf16 {%0, %1, %2, %3, %4, %5, %6, %7, %8, %9, %10, %11, %12, %13, %14, %15, %16, %17, %18, %19, %20, %21, %22, %23, %24, %25, %26, %27, %28, %29, %30, %31}, %32, %33, p, 1, 1, 0, 0;\n}\n"
    : "=f"(d[0]), "=f"(d[1]), "=f"(d[2]), "=f"(d[3]), "=f"(d[4]), "=f"(d[5]), "=f"(d[6]), "=f"(d[7]), "=f"(d[8]), "=f"(d[9]), "=f"(d[10]), "=f"(d[11]), "=f"(d[12]), "=f"(d[13]), "=f"(d[14]), "=f"(d[15]), "=f"(d[16]), "=f"(d[17]), "=f"(d[18]), "=f"(d[19]), "=f"(d[20]), "=f"(d[21]), "=f"(d[22]), "=f"(d[23]), "=f"(d[24]), "=f"(d[25]), "=f"(d[26]), "=f"(d[27]), "=f"(d[28]), "=f"(d[29]), "=f"(d[30]), "=f"(d[31])
    : "l"(da), "l"(db));
}
__device__ __forceinline__ void wgmma_rs_n24_t1(float (&d)[12], uint32_t a0, uint32_t a1, uint32_t a2, uint32_t a3, uint64_t db, int sd) {
  asm volatile("{\n.reg .pred p;\nsetp.ne.b32 p, %17, 0;\n"
    "wgmma.mma_async.sync.aligned.m64n24k16.f32.bf16.bf16 {%0, %1, %2, %3, %4, %5, %6, %7, %8, %9, %10, %11}, {%12, %13, %14, %15}, %16, p, 1, 1, 1;\n}\n"
    : "+f"(d[0]), "+f"(d[1]), "+f"(d[2]), "+f"(d[3]), "+f"(d[4]), "+f"(d[5]), "+f"(d[6]), "+f"(d[7]), "+f"(d[8]), "+f"(d[9]), "+f"(d[10]), "+f"(d[11])
    : "r"(a0), "r"(a1), "r"(a2), "r"(a3), "l"(db), "r"(sd));
}

constexpr int K1_NST = 4;
constexpr int NPROD = 2;
constexpr uint32_t PF0 = 128;
constexpr int K1_A_BYTES = 10 * 16384;
constexpr int K1_SMEM = K1_A_BYTES + K1_NST * 16384 + 1024 + 1024;

template <int BN, bool UNROLL, typename MMA, typename SIDE>
__device__ __forceinline__ void k1_mainloop(float (&acc)[BN / 2], MMA mma, SIDE side, uint32_t sA, uint32_t sB, uint32_t barA, uint32_t barF,
                                            uint32_t barE, uint32_t barE_peer, int it0, bool waitA, int wgi, bool elect) {
  const uint64_t dA0 = mk_desc(sA + wgi * 8192, 16, 1024, 1);
  const uint64_t dB0 = mk_desc(sB, 4096, 1024, 1);
  fence_regs(acc);
#pragma unroll(UNROLL ? 20 : 1)
  for (int s = 0; s < 20; s++) {
    const int it = it0 + s, st = it & (K1_NST - 1);
    if (waitA && !(s & 1)) mbar_wait(barA + 8 * (s >> 1), 0);
    mbar_wait(barF + 8 * st, (it / K1_NST) & 1);
    const uint64_t da = dA0 + (uint32_t)((s >> 1) * 1024 + (s & 1) * 4);
    const uint64_t db = dB0 + (uint32_t)(st * 1024);
    wg_fence();
    mma(acc, da, db, s);
    mma(acc, da + 2, db + 128, 1);
    wg_commit();
    side(s);
    if (s > 0) {
      wg_wait<1>();
      if (elect) { const int ps = (it - 1) & (K1_NST - 1); mbar_arrive_cluster(barE + 8 * ps); mbar_arrive_cluster(barE_peer + 8 * ps); }
    }
  }
  wg_wait<0>();
  fence_regs(acc);
  if (elect) { const int ps = (it0 + 19) & (K1_NST - 1); mbar_arrive_cluster(barE + 8 * ps); mbar_arrive_cluster(barE_peer + 8 * ps); }
}

__device__ __forceinline__ void st32(uint8_t* p, uint32_t v) { *reinterpret_cast<uint32_t*>(p) = v; }

__device__ __forceinline__ void k1_qkv_pack(const float (&acc)[120], uint32_t (&pk)[60], int slot0, int slab, int lane) {
  const bool lo2 = (lane & 3) < 2;
#pragma unroll
  for (int hp = 0; hp < 6; hp++) {
    const float sc0 = slot0 + 2 * hp < 32 ? 0.32259642f : 1.0f;
    float q[5][2];
#pragma unroll
    for (int jj = 0; jj < 5; jj++) {
      const int j = hp * 5 + jj;
      const float v0 = acc[4 * j] * sc0, v1 = acc[4 * j + 1] * sc0, v2 = acc[4 * j + 2] * sc0, v3 = acc[4 * j + 3] * sc0;
      pk[2 * j] = pack_bf16(v0, v1);
      pk[2 * j + 1] = pack_bf16(v2, v3);
      q[jj][0] = fmaf(v0, v0, v1 * v1);
      q[jj][1] = fmaf(v2, v2, v3 * v3);
    }
    uint32_t na = 0, nb = 0;
#pragma unroll
    for (int r = 0; r < 2; r++) {
      float a = q[0][r] + q[1][r] + (lo2 ? q[2][r] : 0.f), b = q[3][r] + q[4][r] + (lo2 ? 0.f : q[2][r]);
      a += __shfl_xor_sync(0xffffffffu, a, 1); b += __shfl_xor_sync(0xffffffffu, b, 1);
      a += __shfl_xor_sync(0xffffffffu, a, 2); b += __shfl_xor_sync(0xffffffffu, b, 2);
      na = max(na, __float_as_uint(a)); nb = max(nb, __float_as_uint(b));
    }
    na = __reduce_max_sync(0xffffffffu, na);
    nb = __reduce_max_sync(0xffffffffu, nb);
    if (lane < 2) g_norm[(slot0 + 2 * hp + lane) * 128 + slab] = __uint_as_float(lane ? nb : na);
  }
}
__device__ __forceinline__ void k1_qkv_store(const uint32_t (&pk)[60], int hp, int part, int slot0, int grp, int g, int t4) {
  const int slot = slot0 + 2 * hp, which = slot >> 5, head = slot & 31;
  const uint32_t gs = which == 0 ? 512u : 768u, hs = which == 0 ? 131072u : 196608u;
  uint8_t* p0 = g_QKV + (head * hs + grp * gs + g * 16 + (which == 0 ? 0u : (which == 1 ? KV_OFF : KV_OFF + 384u)));
  uint8_t* p1 = p0 + hs;
  const bool lo2 = t4 < 2;
  const int j = hp * 5;
  if (part == 0) {
    st32(p0 + t4 * 4, pk[2 * j]); st32(p0 + t4 * 4 + gs, pk[2 * j + 1]);
    st32(p0 + 128 + t4 * 4, pk[2 * j + 2]); st32(p0 + 128 + t4 * 4 + gs, pk[2 * j + 3]);
  } else if (part == 1) {
    uint8_t* pm = lo2 ? p0 + 256 + t4 * 4 : p1 + (t4 * 4 - 8);
    st32(pm, pk[2 * j + 4]); st32(pm + gs, pk[2 * j + 5]);
    uint8_t* pp = (t4 & 1) ? p1 : p0;
    if (lo2) {
      uint2 c0, c1;
      if (which == 0) { c0 = make_uint2(0x42FB47C0u, 0x0000BDCCu); c1 = c0; }
      else if (which == 1) {
        c0 = ((MUFU_MASK >> (grp & 15)) & 1) ? make_uint2(0u, 0u) : make_uint2(0x3F803F80u, 0x00003F80u);
        c1 = ((MUFU_MASK >> ((grp + 1) & 15)) & 1) ? make_uint2(0u, 0u) : make_uint2(0x3F803F80u, 0x00003F80u);
      } else { c0 = make_uint2(0x00003F80u, 0u); c1 = c0; }
      *reinterpret_cast<uint2*>(pp + 264) = c0;
      *reinterpret_cast<uint2*>(pp + 264 + gs) = c1;
    } else if (which == 0) {
      *reinterpret_cast<uint4*>(pp + 384) = make_uint4(0, 0, 0, 0);
      *reinterpret_cast<uint4*>(pp + 384 + 512) = make_uint4(0, 0, 0, 0);
    }
  } else {
    const uint32_t e2 = lo2 ? 8 + t4 * 4 : 120 + t4 * 4;
    st32(p1 + e2, pk[2 * j + 6]); st32(p1 + e2 + gs, pk[2 * j + 7]);
    st32(p1 + 128 + e2, pk[2 * j + 8]); st32(p1 + 128 + e2 + gs, pk[2 * j + 9]);
  }
}

__global__ void __cluster_dims__(2, 1, 1) __launch_bounds__(384, 1)
k1_proj(const __grid_constant__ CUtensorMap tmX, const __grid_constant__ CUtensorMap tmWqkv, const __grid_constant__ CUtensorMap tmW1,
        const __nv_bfloat16* __restrict__ b1, const __nv_bfloat16* __restrict__ gate_w, const uint8_t* __restrict__ x,
        const uint8_t* __restrict__ wqkv, const uint8_t* __restrict__ w1, const uint8_t* __restrict__ w2, const uint8_t* __restrict__ wo) {
  extern __shared__ uint8_t smem_raw[];
  const uint32_t sb = (smem_u32(smem_raw) + 1023u) & ~1023u;
  const uint32_t sA = sb, sB = sb + K1_A_BYTES, bars = sB + K1_NST * 16384;
  const uint32_t barA = bars, barF = bars + 80, barE = barF + 8 * K1_NST;
  const int tid = threadIdx.x, lane = tid & 31;
  const int warp = __shfl_sync(0xffffffffu, tid >> 5, 0);
  const int rb = blockIdx.x & 15, cg = blockIdx.x >> 4;
  const uint32_t rank = cluster_rank();
  if (tid == 0) {
    STAMP(0);
    prefetch_tmap(&tmX); prefetch_tmap(&tmWqkv); prefetch_tmap(&tmW1);
    for (int i = 0; i < 10; i++) mbar_init(barA + 8 * i, 1);
    for (int i = 0; i < K1_NST; i++) { mbar_init(barF + 8 * i, 1); mbar_init(barE + 8 * i, 16); }
    fence_barrier_init();
    fence_proxy_async();
    for (int i = 0; i < K1_NST; i++) {
      if (!(i & 1)) {
        mbar_expect_tx(barA + 4 * i, 16384);
        tma_2d(sA + (i >> 1) * 16384, &tmX, i * 32, rb * 128, barA + 4 * i);
      }
      mbar_expect_tx(barF + 8 * i, 16384);
      for (int b = 0; b < 4; b++) tma_2d(sB + i * 16384 + b * 4096, &tmWqkv, cg * 240 + b * 64, i * 32, barF + 8 * i);
    }
  }
  pdl_launch();
  __syncwarp();
  cluster_arrive_relaxed();
  cluster_wait();

  if (warp < 4) {
    asm volatile("setmaxnreg.dec.sync.aligned.u32 40;");
    if (warp == 0 || warp == 2) {
      if (lane == 0) {
        if (warp == 2) {
          for (int ka = 2; ka < 4; ka++) {
            mbar_expect_tx(barA + 8 * ka, 16384);
            tma_2d(sA + ka * 16384, &tmX, ka * 64, rb * 128, barA + 8 * ka);
          }
        }
#pragma unroll 1
        for (int it = K1_NST + (warp >> 1); it < 40; it += NPROD) {
          const int st = it & (K1_NST - 1);
          const bool t0 = it < 20;
          const CUtensorMap* m = t0 ? &tmWqkv : &tmW1;
          const int col = (t0 ? cg * 240 : cg * 216) + (int)rank * 128;
          const int k = (t0 ? it : it - 20) * 32;
          const uint32_t dst = sB + st * 16384 + rank * 8192;
          mbar_wait(barE + 8 * st, ((it / K1_NST) - 1) & 1);
          mbar_expect_tx(barF + 8 * st, 16384);
          tma_2d_mc(dst, m, col, k, barF + 8 * st, (uint16_t)3);
          tma_2d_mc(dst + 4096, m, col + 64, k, barF + 8 * st, (uint16_t)3);
          if (it < 10) {
            const int ka = it;
            mbar_expect_tx(barA + 8 * ka, 16384);
            tma_2d(sA + ka * 16384, &tmX, ka * 64, rb * 128, barA + 8 * ka);
          }
        }
      }
    } else if (warp == 3) {
      if (lane == 0) {
        const uint32_t b = blockIdx.x;
        l2_prefetch(wqkv + PF0 * 3840u + b * ((640u - PF0) * 30u), (640u - PF0) * 30u);
        mbar_wait(barA + 8 * 3, 0);
        l2_prefetch(w1 + b * 17280u, 17280u);
        mbar_wait(barA + 8 * 9, 0);
        l2_prefetch(w2 + b * 17280u, 17280u);
        l2_prefetch(wo + b * 6400u, 6400u);
      }
    } else if (warp == 1) {
      const int r = cg * 16 + (lane >> 1), half = lane & 1;
      float acc = 0.f;
      mbar_wait(barA + 72, 0);
#pragma unroll 1
      for (int kb = half * 5; kb < half * 5 + 5; kb++) {
        mbar_wait(barA + 8 * kb, 0);
#pragma unroll
        for (int c = 0; c < 8; c++) {
          uint4 xv;
          asm volatile("ld.shared.v4.u32 {%0,%1,%2,%3}, [%4];" : "=r"(xv.x), "=r"(xv.y), "=r"(xv.z), "=r"(xv.w)
                       : "r"(sA + kb * 16384 + r * 128 + ((c ^ (r & 7)) << 4)));
          const uint4 wv = __ldg(reinterpret_cast<const uint4*>(gate_w + kb * 64 + c * 8));
          acc = fmaf(bf_lo(xv.x), bf_lo(wv.x), acc); acc = fmaf(bf_hi(xv.x), bf_hi(wv.x), acc);
          acc = fmaf(bf_lo(xv.y), bf_lo(wv.y), acc); acc = fmaf(bf_hi(xv.y), bf_hi(wv.y), acc);
          acc = fmaf(bf_lo(xv.z), bf_lo(wv.z), acc); acc = fmaf(bf_hi(xv.z), bf_hi(wv.z), acc);
          acc = fmaf(bf_lo(xv.w), bf_lo(wv.w), acc); acc = fmaf(bf_hi(xv.w), bf_hi(wv.w), acc);
        }
      }
      acc += __shfl_xor_sync(0xffffffffu, acc, 1);
      if (!half) g_gate[rb * 128 + r] = 1.f / (1.f + __expf(-acc));
    }
  } else {
    const int wgi = (warp >> 2) - 1, wq = warp & 3, g = lane >> 2, t4 = lane & 3;
    const uint32_t barE_self = mapa(barE, rank), barE_peer = mapa(barE, rank ^ 1);
    const bool elect = lane == 0;
    asm volatile("setmaxnreg.inc.sync.aligned.u32 232;");
    uint32_t pk[60];
    const int grp = rb * 16 + wgi * 8 + wq * 2, slot0 = cg * 12;
    {
      float acc[120];
      k1_mainloop<240, false>(acc, [](float (&d)[120], uint64_t a, uint64_t b, int sd) { wgmma_ssp_n240_t01(d, a, b, sd); }, [](int) {},
                              sA, sB, barA, barF, barE_self, barE_peer, 0, true, wgi, elect);
      if (warp == 4) STAMP(1);
      k1_qkv_pack(acc, pk, slot0, rb * 8 + wgi * 4 + wq, lane);
    }
    if (warp == 4) STAMP(2);
    {
      float acc[108];
      k1_mainloop<216, true>(acc, [](float (&d)[108], uint64_t a, uint64_t b, int sd) { wgmma_ssp_n216_t01(d, a, b, sd); },
                             [&](int s) {
                               if (s < 18) k1_qkv_store(pk, s / 3, s % 3, slot0, grp, g, t4);
                             },
                             sA, sB, barA, barF, barE_self, barE_peer, 20, false, wgi, elect);
      if (warp == 8) STAMP(3);
      uint8_t* base = g_A2 + ((size_t)(rb * 296 + cg * 27) * 16 + wgi * 8 + wq * 2) * 128 + g * 16 + t4 * 4;
      const uint32_t* bp = reinterpret_cast<const uint32_t*>(b1 + cg * 216 + t4 * 2);
#pragma unroll
      for (int j = 0; j < 27; j++) {
        const uint32_t bv = __ldg(bp + j * 4);
        const float c0 = bf_lo(bv), c1 = bf_hi(bv);
        const float h0 = fmaxf(acc[4 * j] + c0, 0.f), h1 = fmaxf(acc[4 * j + 1] + c1, 0.f);
        const float h2 = fmaxf(acc[4 * j + 2] + c0, 0.f), h3 = fmaxf(acc[4 * j + 3] + c1, 0.f);
        st32(base + j * 2048, pack_bf16(h0 * h0, h1 * h1));
        st32(base + j * 2048 + 128, pack_bf16(h2 * h2, h3 * h3));
      }
    }
    if (warp == 8) STAMP(4);
  }
  __syncwarp();
  cluster_arrive_relaxed();
  cluster_wait();
}

constexpr int KV_HEAD_BYTES = 256 * 768, Q_BYTES = 8 * 4096;
constexpr int AT_NCHUNK = 16, AT_CHUNK_BYTES = KV_HEAD_BYTES / AT_NCHUNK;
constexpr int AT_SMEM = KV_HEAD_BYTES + Q_BYTES + 1024 + 1024;

template <int T0, int T1, int TOFF>
__device__ __forceinline__ void exp_tiles(const float (&s)[32], uint32_t (&p)[16], uint32_t cmask, uint32_t cone) {
#pragma unroll
  for (int t = T0; t < T1; t++) {
#pragma unroll
    for (int h = 0; h < 2; h++) {
      const float x0 = s[4 * t + 2 * h], x1 = s[4 * t + 2 * h + 1];
      uint32_t r;
      if ((MUFU_MASK >> ((t + TOFF) & 15)) & 1) {
        r = pack_bf16(ex2(x0), ex2(x1));
      } else {
        const uint32_t u = __byte_perm(__float_as_uint(x0), __float_as_uint(x1), 0x5410);
        uint32_t g;
        asm("lop3.b32 %0, %1, %2, %3, 0xEA;" : "=r"(g) : "r"(u), "r"(cmask), "r"(cone));
        r = hfma2_bf16(g, g, 0x40034003u) + u - g;
      }
      p[2 * t + h] = r;
      asm volatile("" : "+r"(p[2 * t + h])::"memory");
    }
  }
}
template <int TOFF>
__device__ __forceinline__ void exp_pv(const float (&s)[32], uint32_t (&p)[16], float (&o)[12], uint64_t dv, int sd, uint32_t cmask, uint32_t cone) {
  exp_tiles<0, 4, TOFF>(s, p, cmask, cone);
  wg_fence();
  wgmma_rs_n24_t1(o, p[0], p[1], p[2], p[3], dv, sd);
  wgmma_rs_n24_t1(o, p[4], p[5], p[6], p[7], dv + 96, 1);
  exp_tiles<4, 8, TOFF>(s, p, cmask, cone);
  wg_fence();
  wgmma_rs_n24_t1(o, p[8], p[9], p[10], p[11], dv + 192, 1);
  wgmma_rs_n24_t1(o, p[12], p[13], p[14], p[15], dv + 288, 1);
}
__device__ __forceinline__ void qk64(float (&s)[32], uint64_t dq, uint64_t dk) {
  wgmma_ss0_n64_t00(s, dq, dk);
  wgmma_ss_n64_t00(s, dq + 16, dk + 16);
}
__device__ __forceinline__ void attn_store(const float (&o)[12], int row0, int head, int lane) {
  const int t4 = lane & 3;
  const float l0 = __shfl_sync(0xffffffffu, o[8], (lane & ~3) | 2), l1 = __shfl_sync(0xffffffffu, o[10], (lane & ~3) | 2);
  const float r0 = __fdividef(g_gate[row0], l0), r1 = __fdividef(g_gate[row0 + 8], l1);
  uint8_t* base = g_A2 + ((size_t)((row0 >> 7) * 296 + 216) * 16 + ((row0 & 127) >> 3)) * 128 + (row0 & 7) * 16;
#pragma unroll
  for (int tt = 0; tt < 3; tt++) {
    const int d = tt * 8 + 2 * t4;
    if (d < 20) {
      const int col = head * 20 + d;
      uint8_t* ptr = base + (col >> 3) * 2048 + (col & 7) * 2;
      *reinterpret_cast<uint32_t*>(ptr) = pack_bf16(o[4 * tt] * r0, o[4 * tt + 1] * r0);
      *reinterpret_cast<uint32_t*>(ptr + 128) = pack_bf16(o[4 * tt + 2] * r1, o[4 * tt + 3] * r1);
    }
  }
}

__device__ __forceinline__ void attn_slow(uint32_t sb, uint32_t bb, int wg, int rowbase, int head, int lane) {
  const uint64_t dk0 = mk_desc(sb, 128, 768, 0), dv0 = mk_desc(sb + 384, 768, 128, 0);
  const uint64_t dq0 = mk_desc(sb + KV_HEAD_BYTES + wg * 8192, 128, 512, 0);
#pragma unroll 1
  for (int mt = 0; mt < 2; mt++) {
    float o[12], s[32];
    uint32_t p[16];
#pragma unroll
    for (int i = 0; i < 12; i++) o[i] = 0.f;
    float m0 = -INFINITY, m1 = -INFINITY;
#pragma unroll 1
    for (int b = 0; b < 32; b++) {
      if (mt == 0 && !(b & 1)) mbar_wait(bb + 8 * (b >> 1), 0);
      wg_fence();
      qk64(s, dq0 + (uint32_t)(mt * 256), dk0 + (uint32_t)(b * 384));
      wg_commit();
      wg_wait<0>();
      fence_regs(s);
      float n0 = m0, n1 = m1;
#pragma unroll
      for (int t = 0; t < 8; t++) { n0 = fmaxf(n0, fmaxf(s[4 * t], s[4 * t + 1])); n1 = fmaxf(n1, fmaxf(s[4 * t + 2], s[4 * t + 3])); }
      n0 = fmaxf(n0, __shfl_xor_sync(0xffffffffu, n0, 1)); n0 = fmaxf(n0, __shfl_xor_sync(0xffffffffu, n0, 2));
      n1 = fmaxf(n1, __shfl_xor_sync(0xffffffffu, n1, 1)); n1 = fmaxf(n1, __shfl_xor_sync(0xffffffffu, n1, 2));
      const float a0 = ex2(m0 - n0), a1 = ex2(m1 - n1);
      m0 = n0; m1 = n1;
#pragma unroll
      for (int t = 0; t < 3; t++) { o[4 * t] *= a0; o[4 * t + 1] *= a0; o[4 * t + 2] *= a1; o[4 * t + 3] *= a1; }
#pragma unroll
      for (int t = 0; t < 8; t++) {
        p[2 * t] = pack_bf16(ex2(s[4 * t] - m0), ex2(s[4 * t + 1] - m0));
        p[2 * t + 1] = pack_bf16(ex2(s[4 * t + 2] - m1), ex2(s[4 * t + 3] - m1));
      }
      fence_regs(o);
      wg_fence();
#pragma unroll
      for (int k = 0; k < 4; k++) wgmma_rs_n24_t1(o, p[4 * k], p[4 * k + 1], p[4 * k + 2], p[4 * k + 3], dv0 + (uint32_t)(b * 384 + k * 96), 1);
      wg_commit();
      wg_wait<0>();
      fence_regs(o);
    }
    attn_store(o, rowbase + mt * 64, head, lane);
  }
}

__global__ void __launch_bounds__(512, 1) k2_attn(int opaque_zero) {
  extern __shared__ uint8_t smem_raw[];
  const uint32_t sb = (smem_u32(smem_raw) + 1023u) & ~1023u;
  const uint32_t bb = sb + KV_HEAD_BYTES + Q_BYTES;
  const int tid = threadIdx.x, lane = tid & 31;
  const int warp = __shfl_sync(0xffffffffu, tid >> 5, 0), wg = warp >> 2;
  const int head = blockIdx.x >> 2, qb = blockIdx.x & 3;
  if (tid == 0) {
    STAMP(5);
    for (int i = 0; i <= AT_NCHUNK; i++) mbar_init(bb + 8 * i, 1);
    fence_barrier_init();
    fence_proxy_async();
  }
  pdl_launch();
  pdl_wait();
  if (tid == 0) {
    STAMP(6);
    mbar_expect_tx(bb + 8 * AT_NCHUNK, Q_BYTES);
    bulk_g2s(sb + KV_HEAD_BYTES, g_QKV + (size_t)blockIdx.x * Q_BYTES, Q_BYTES, bb + 8 * AT_NCHUNK);
    for (int i = 0; i < AT_NCHUNK; i++) {
      mbar_expect_tx(bb + 8 * i, AT_CHUNK_BYTES);
      bulk_g2s(sb + i * AT_CHUNK_BYTES, g_QKV + KV_OFF + (size_t)head * KV_HEAD_BYTES + i * AT_CHUNK_BYTES, AT_CHUNK_BYTES, bb + 8 * i);
    }
  }
  bool fast;
  {
    const uint32_t* nb = reinterpret_cast<const uint32_t*>(g_norm);
    const uint4 k4 = *reinterpret_cast<const uint4*>(nb + (32 + head) * 128 + lane * 4);
    const uint4 v4 = *reinterpret_cast<const uint4*>(nb + (64 + head) * 128 + lane * 4);
    const float nq = __uint_as_float(__reduce_max_sync(0xffffffffu, nb[head * 128 + qb * 32 + lane]));
    const float nk = __uint_as_float(__reduce_max_sync(0xffffffffu, max(max(k4.x, k4.y), max(k4.z, k4.w))));
    const float nv = __uint_as_float(__reduce_max_sync(0xffffffffu, max(max(v4.x, v4.y), max(v4.z, v4.w))));
    fast = (nq * nk <= 2304.0f) && (nq <= 1e30f) && (nk <= 1e30f) && (nv <= 1e30f) && (nv >= 1e-18f);
  }
  const int rowbase = qb * 512 + wg * 128 + (warp & 3) * 16 + (lane >> 2);
  __syncthreads();
  mbar_wait(bb + 8 * AT_NCHUNK, 0);
  if (!fast) {
    *reinterpret_cast<uint2*>(smem_raw + (sb - smem_u32(smem_raw)) + KV_HEAD_BYTES + (tid >> 3) * 512 + 256 + (tid & 7) * 16 + 8) = make_uint2(0u, 0u);
    fence_proxy_async();
    __syncthreads();
    attn_slow(sb, bb, wg, rowbase, head, lane);
    return;
  }
  uint32_t cmask = 0x007F007Fu + opaque_zero, cone = 0x3F803F80u + opaque_zero;
  const uint64_t dk0 = mk_desc(sb, 128, 768, 0), dv0 = mk_desc(sb + 384, 768, 128, 0);
  const uint64_t dq0 = mk_desc(sb + KV_HEAD_BYTES + wg * 8192, 128, 512, 0);
  float o[12], s0[32], s1[32];
  uint32_t p0[16], p1[16];
#pragma unroll
  for (int i = 0; i < 12; i++) o[i] = 0.f;
  fence_regs(o);
  mbar_wait(bb, 0);
  wg_fence();
  qk64(s0, dq0, dk0);
  wg_commit();
  wg_wait<0>();
  fence_regs(s0);
#pragma unroll 1
  for (int it = 0; it < 32; it++) {
    const int c = it & 15, mt = it >> 4;
    const uint64_t dq = dq0 + (uint32_t)(mt * 256);
    const uint32_t off = c * 768;
    wg_fence();
    qk64(s1, dq, dk0 + (off + 384));
    wg_commit();
    exp_pv<0>(s0, p0, o, dv0 + off, c, cmask, cone);
    wg_commit();
    wg_wait<1>();
    fence_regs(s1);
    const int cn = (c + 1) & 15;
    const uint64_t dqn = dq0 + (uint32_t)((((it + 1) >> 4) & 1) * 256);
    if (it < 15) mbar_wait(bb + 8 * cn, 0);
    wg_fence();
    qk64(s0, dqn, dk0 + (uint32_t)(cn * 768));
    wg_commit();
    exp_pv<8>(s1, p1, o, dv0 + (off + 384), 1, cmask, cone);
    wg_commit();
    wg_wait<0>();
    fence_regs(s0);
    fence_regs(o);
    if (c == 15) attn_store(o, rowbase + mt * 64, head, lane);
  }
  if (warp == 0) STAMP(8);
}

constexpr int K3_NST = 6, K3_STAGE = 8192 + 10240;
constexpr int K3_RED = 128 * 80 * 4;
constexpr int K3_SMEM = K3_NST * K3_STAGE + 1024 + 1024;

__global__ void __cluster_dims__(4, 1, 1) __maxnreg__(112)
k3_out(const __grid_constant__ CUtensorMap tmW2, const __grid_constant__ CUtensorMap tmWo, const __nv_bfloat16* __restrict__ b2,
       __nv_bfloat16* __restrict__ out) {
  extern __shared__ uint8_t smem_raw[];
  const uint32_t sb = (smem_u32(smem_raw) + 1023u) & ~1023u;
  const uint32_t barF = sb + K3_NST * K3_STAGE, barE = barF + 8 * K3_NST, barR = barE + 8 * K3_NST, barX = barR + 8;
  const int tid = threadIdx.x, lane = tid & 31;
  const int warp = __shfl_sync(0xffffffffu, tid >> 5, 0);
  const uint32_t rank = cluster_rank(), ks = rank & 1, rp = rank >> 1;
  const int cid = blockIdx.x >> 2, rb = (cid >> 2) * 2 + rp, ct = cid & 3;
  if (tid == 0) {
    STAMP(9);
    prefetch_tmap(&tmW2); prefetch_tmap(&tmWo);
    for (int i = 0; i < K3_NST; i++) { mbar_init(barF + 8 * i, 1); mbar_init(barE + 8 * i, 16); }
    mbar_init(barR, 1);
    mbar_init(barX, 8);
    fence_barrier_init();
    mbar_expect_tx(barR, K3_RED);
  }
  __syncwarp();
  cluster_arrive_relaxed();
  cluster_wait();
  if (warp == 8) {
    if (lane == 0) {
      const int s0 = ks * 37;
      const uint16_t mask = (uint16_t)(5u << ks);
      const uint8_t* asrc = g_A2 + (size_t)rb * 296 * 2048;
      int st = 0, ph = 1;
#pragma unroll 1
      for (int i = 0; i < 37; i++) {
        const int s = s0 + i;
        if (i == K3_NST) {
          pdl_wait();
          for (int q = 0; q < K3_NST; q++) bulk_g2s(sb + q * K3_STAGE, asrc + (size_t)(s0 + q) * 8192, 8192, barF + 8 * q);
        }
        if (i >= K3_NST) mbar_wait(barE + 8 * st, ph);
        mbar_expect_tx(barF + 8 * st, K3_STAGE);
        if (i >= K3_NST) bulk_g2s(sb + st * K3_STAGE, asrc + (size_t)s * 8192, 8192, barF + 8 * st);
        const CUtensorMap* m = s < 54 ? &tmW2 : &tmWo;
        const int k = (s < 54 ? s : s - 54) * 32;
        const int split = 2 + (i & 1);
        const int b0 = rp ? split : 0, b1 = rp ? 5 : split;
        for (int b = b0; b < b1; b++) tma_2d_mc(sb + st * K3_STAGE + 8192 + b * 2048, m, ct * 160 + b * 32, k, barF + 8 * st, mask);
        if (++st == K3_NST) { st = 0; ph ^= 1; }
      }
    }
  } else {
    const int wgi = warp >> 2, wq = warp & 3, g = lane >> 2, t4 = lane & 3;
    const int rloc = wgi * 64 + wq * 16 + g, row = rb * 128 + rloc;
    const int col0 = ct * 160 + ks * 80 + t4 * 2;
    const uint32_t barE_self = mapa(barE, rank), barE_peer = mapa(barE, rank ^ 2);
    pdl_wait();
    if (warp == 0) STAMP(10);
    const float w0 = 1.f - g_gate[row], w1 = 1.f - g_gate[row + 8];
    float acc[80];
    const uint64_t dA0 = mk_desc(sb + wgi * 1024, 2048, 128, 0), dB0 = mk_desc(sb + 8192, 2048, 512, 2);
    const int nsw = ks ? 17 : 37;
    int st = 0, ph = 0, pst = 0;
    fence_regs(acc);
#pragma unroll 1
    for (int i = 0; i < 37; i++) {
      mbar_wait(barF + 8 * st, ph);
      const uint32_t off = st * (K3_STAGE >> 4);
      wg_fence();
      wgmma_ssp_n160_t01(acc, dA0 + off, dB0 + off, i);
      wgmma_ssp_n160_t01(acc, dA0 + off + 256, dB0 + off + 64, 1);
      wg_commit();
      if (i + 1 == nsw) {
        wg_wait<0>();
        fence_regs(acc);
#pragma unroll
        for (int j = 0; j < 20; j++) { acc[4 * j] *= w0; acc[4 * j + 1] *= w0; acc[4 * j + 2] *= w1; acc[4 * j + 3] *= w1; }
        fence_regs(acc);
      } else {
        wg_wait<1>();
      }
      if (i > 0 && i < 37 - K3_NST + 1 && lane == 0) { mbar_arrive_cluster(barE_self + 8 * pst); mbar_arrive_cluster(barE_peer + 8 * pst); }
      pst = st;
      if (++st == K3_NST) { st = 0; ph ^= 1; }
    }
    wg_wait<0>();
    fence_regs(acc);
    if (warp == 0) STAMP(11);
    if (lane == 0) mbar_arrive_cluster(mapa(barX, rank ^ 1));
    uint32_t bias[10];
#pragma unroll
    for (int j = 0; j < 10; j++) bias[j] = __ldg(reinterpret_cast<const uint32_t*>(b2 + col0 + j * 8));
    const uint32_t peerRed = mapa(sb, rank ^ 1) + tid * 16, peerBar = mapa(barR, rank ^ 1);
    mbar_wait(barX, 0);
#pragma unroll
    for (int j = 0; j < 10; j++) {
      const float a0 = ks ? acc[4 * j] : acc[40 + 4 * j], a1 = ks ? acc[4 * j + 1] : acc[40 + 4 * j + 1];
      const float a2 = ks ? acc[4 * j + 2] : acc[40 + 4 * j + 2], a3 = ks ? acc[4 * j + 3] : acc[40 + 4 * j + 3];
      asm volatile("st.async.weak.shared::cluster.mbarrier::complete_tx::bytes.v4.f32 [%0], {%1, %2, %3, %4}, [%5];"
                   ::"r"(peerRed + j * 4096), "f"(a0), "f"(a1), "f"(a2), "f"(a3), "r"(peerBar) : "memory");
    }
    mbar_wait(barR, 0);
    if (warp == 0) STAMP(13);
#pragma unroll
    for (int j = 0; j < 10; j++) {
      float p0, p1, p2, p3;
      asm volatile("ld.shared.v4.f32 {%0, %1, %2, %3}, [%4];" : "=f"(p0), "=f"(p1), "=f"(p2), "=f"(p3) : "r"(sb + tid * 16 + j * 4096));
      const float a0 = ks ? acc[40 + 4 * j] : acc[4 * j], a1 = ks ? acc[40 + 4 * j + 1] : acc[4 * j + 1];
      const float a2 = ks ? acc[40 + 4 * j + 2] : acc[4 * j + 2], a3 = ks ? acc[40 + 4 * j + 3] : acc[4 * j + 3];
      const float c0 = bf_lo(bias[j]), c1 = bf_hi(bias[j]);
      *reinterpret_cast<uint32_t*>(out + (size_t)row * D_ + col0 + j * 8) = pack_bf16(fmaf(w0, c0, a0 + p0), fmaf(w0, c1, a1 + p1));
      *reinterpret_cast<uint32_t*>(out + (size_t)(row + 8) * D_ + col0 + j * 8) = pack_bf16(fmaf(w1, c0, a2 + p2), fmaf(w1, c1, a3 + p3));
    }
    if (warp == 0) STAMP(12);
  }
}

typedef CUresult (*EncodeFn)(CUtensorMap*, CUtensorMapDataType, cuuint32_t, void*, const cuuint64_t*, const cuuint64_t*, const cuuint32_t*,
                             const cuuint32_t*, CUtensorMapInterleave, CUtensorMapSwizzle, CUtensorMapL2promotion, CUtensorMapFloatOOBfill);

void make_map(EncodeFn fn, CUtensorMap* m, const void* ptr, uint64_t inner, uint64_t outer, uint32_t box_inner, uint32_t box_outer, CUtensorMapSwizzle sw) {
  cuuint64_t dims[2] = {inner, outer};
  cuuint64_t strides[1] = {inner * 2};
  cuuint32_t box[2] = {box_inner, box_outer};
  cuuint32_t es[2] = {1, 1};
  fn(m, CU_TENSOR_MAP_DATA_TYPE_BFLOAT16, 2, const_cast<void*>(ptr), dims, strides, box, es, CU_TENSOR_MAP_INTERLEAVE_NONE, sw,
     CU_TENSOR_MAP_L2_PROMOTION_L2_256B, CU_TENSOR_MAP_FLOAT_OOB_FILL_NONE);
}

}

extern "C" void kernel_launch(void* const* d_in, const int* in_sizes, int n_in, void* d_out, int out_size) {
  (void)in_sizes; (void)n_in; (void)out_size;
  const __nv_bfloat16* x = (const __nv_bfloat16*)d_in[0];
  const __nv_bfloat16* wqkv = (const __nv_bfloat16*)d_in[1];
  const __nv_bfloat16* wo = (const __nv_bfloat16*)d_in[2];
  const __nv_bfloat16* w1 = (const __nv_bfloat16*)d_in[4];
  const __nv_bfloat16* b1 = (const __nv_bfloat16*)d_in[5];
  const __nv_bfloat16* w2 = (const __nv_bfloat16*)d_in[6];
  const __nv_bfloat16* b2 = (const __nv_bfloat16*)d_in[7];
  const __nv_bfloat16* gw = (const __nv_bfloat16*)d_in[8];

  static EncodeFn enc = nullptr;
  if (!enc) {
    void* p = nullptr;
    cudaDriverEntryPointQueryResult qr;
    cudaGetDriverEntryPoint("cuTensorMapEncodeTiled", &p, cudaEnableDefault, &qr);
    enc = (EncodeFn)p;
    cudaFuncSetAttribute(k1_proj, cudaFuncAttributeMaxDynamicSharedMemorySize, K1_SMEM);
    cudaFuncSetAttribute(k2_attn, cudaFuncAttributeMaxDynamicSharedMemorySize, AT_SMEM);
    cudaFuncSetAttribute(k3_out, cudaFuncAttributeMaxDynamicSharedMemorySize, K3_SMEM);
  }
  CUtensorMap tmX, tmWqkv, tmW1, tmW2, tmWo;
  make_map(enc, &tmX, x, D_, S_, 64, 128, CU_TENSOR_MAP_SWIZZLE_128B);
  make_map(enc, &tmWqkv, wqkv, 3 * D_, D_, 64, 32, CU_TENSOR_MAP_SWIZZLE_128B);
  make_map(enc, &tmW1, w1, F_, D_, 64, 32, CU_TENSOR_MAP_SWIZZLE_128B);
  make_map(enc, &tmW2, w2, D_, F_, 32, 32, CU_TENSOR_MAP_SWIZZLE_64B);
  make_map(enc, &tmWo, wo, D_, D_, 32, 32, CU_TENSOR_MAP_SWIZZLE_64B);

  cudaStream_t st = cudaStreamPerThread;
  k1_proj<<<128, 384, K1_SMEM, st>>>(tmX, tmWqkv, tmW1, b1, gw, (const uint8_t*)x, (const uint8_t*)wqkv, (const uint8_t*)w1,
                                     (const uint8_t*)w2, (const uint8_t*)wo);

  cudaLaunchAttribute at[1];
  at[0].id = cudaLaunchAttributeProgrammaticStreamSerialization;
  at[0].val.programmaticStreamSerializationAllowed = 1;
  {
    cudaLaunchConfig_t cfg = {};
    cfg.gridDim = dim3(128); cfg.blockDim = dim3(512); cfg.dynamicSmemBytes = AT_SMEM; cfg.stream = st;
    cfg.attrs = at; cfg.numAttrs = 1;
    cudaLaunchKernelEx(&cfg, k2_attn, 0);
  }
  {
    cudaLaunchConfig_t cfg = {};
    cfg.gridDim = dim3(128); cfg.blockDim = dim3(288); cfg.dynamicSmemBytes = K3_SMEM; cfg.stream = st;
    cfg.attrs = at; cfg.numAttrs = 1;
    cudaLaunchKernelEx(&cfg, k3_out, tmW2, tmWo, b2, (__nv_bfloat16*)d_out);
  }
}
```

```cpp
#include <cuda_runtime.h>
#include <cuda_bf16.h>
#include <cuda.h>
#include <stdint.h>
#include <type_traits>

namespace {

constexpr int S_ = 2048, D_ = 640, NH = 32, F_ = 1728;

constexpr uint32_t KV_OFF = NH * 256 * 512;
__device__ __align__(1024) uint8_t g_QKV[NH * 256 * 512 + NH * 256 * 768];
__device__ __align__(1024) uint8_t g_A2[16 * 296 * 2048];
__device__ float g_gate[S_];
__device__ __align__(16) float g_norm[96 * 128];

constexpr uint32_t MUFU_MASK = 0x4925u;

__device__ __forceinline__ uint32_t smem_u32(const void* p) { return (uint32_t)__cvta_generic_to_shared(p); }
__device__ __forceinline__ void wg_fence() { asm volatile("wgmma.fence.sync.aligned;" ::: "memory"); }
__device__ __forceinline__ void wg_commit() { asm volatile("wgmma.commit_group.sync.aligned;" ::: "memory"); }
template <int N> __device__ __forceinline__ void wg_wait() { asm volatile("wgmma.wait_group.sync.aligned %0;" ::"n"(N) : "memory"); }
template <int N> __device__ __forceinline__ void fence_regs(float (&r)[N]) {
#pragma unroll
  for (int i = 0; i < N; i++) asm volatile("" : "+f"(r[i])::"memory");
}
__device__ __forceinline__ float ex2(float x) { float y; asm("ex2.approx.ftz.f32 %0, %1;" : "=f"(y) : "f"(x)); return y; }
__device__ __forceinline__ uint32_t pack_bf16(float lo, float hi) { uint32_t y; asm("cvt.rn.bf16x2.f32 %0, %1, %2;" : "=r"(y) : "f"(hi), "f"(lo)); return y; }
__device__ __forceinline__ uint32_t hfma2_bf16(uint32_t a, uint32_t b, uint32_t c) { uint32_t y; asm("fma.rn.bf16x2 %0, %1, %2, %3;" : "=r"(y) : "r"(a), "r"(b), "r"(c)); return y; }
__device__ __forceinline__ float bf_lo(uint32_t v) { return __uint_as_float(v << 16); }
__device__ __forceinline__ float bf_hi(uint32_t v) { return __uint_as_float(v & 0xffff0000u); }
__device__ __forceinline__ void mbar_init(uint32_t bar, int cnt) { asm volatile("mbarrier.init.shared::cta.b64 [%0], %1;" ::"r"(bar), "r"(cnt)); }
__device__ __forceinline__ void mbar_expect_tx(uint32_t bar, uint32_t bytes) { asm volatile("mbarrier.arrive.expect_tx.shared::cta.b64 _, [%0], %1;" ::"r"(bar), "r"(bytes) : "memory"); }
__device__ __forceinline__ void mbar_arrive(uint32_t bar) { asm volatile("mbarrier.arrive.shared::cta.b64 _, [%0];" ::"r"(bar) : "memory"); }
__device__ __forceinline__ void mbar_arrive_cluster(uint32_t cluster_addr) { asm volatile("mbarrier.arrive.shared::cluster.b64 _, [%0];" ::"r"(cluster_addr) : "memory"); }
__device__ __forceinline__ void mbar_wait(uint32_t bar, uint32_t parity) {
  asm volatile(
      "{\n.reg .pred p;\n.reg .u32 n;\n"
      "mbarrier.try_wait.parity.shared::cta.b64 p, [%0], %1;\n"
      "@p bra DONE;\n"
      "mov.u32 n, 0;\n"
      "LOOP:\n"
      "mbarrier.try_wait.parity.shared::cta.b64 p, [%0], %1;\n"
      "@p bra DONE;\n"
      "add.u32 n, n, 1;\n"
      "setp.lt.u32 p, n, 0x1000000;\n"
      "@p bra LOOP;\n"
      "trap;\n"
      "DONE:\n}\n" ::"r"(bar), "r"(parity) : "memory");
}
__device__ __forceinline__ void bulk_g2s(uint32_t dst, const void* src, uint32_t bytes, uint32_t bar) {
  asm volatile("cp.async.bulk.shared::cluster.global.mbarrier::complete_tx::bytes [%0], [%1], %2, [%3];" ::"r"(dst), "l"(src), "r"(bytes), "r"(bar) : "memory");
}
__device__ __forceinline__ void l2_prefetch(const void* src, uint32_t bytes) {
  asm volatile("cp.async.bulk.prefetch.L2.global [%0], %1;" ::"l"(src), "r"(bytes) : "memory");
}
__device__ __forceinline__ void tma_2d(uint32_t dst, const CUtensorMap* m, int c0, int c1, uint32_t bar) {
  asm volatile("cp.async.bulk.tensor.2d.shared::cluster.global.mbarrier::complete_tx::bytes [%0], [%1, {%3, %4}], [%2];" ::"r"(dst), "l"(m), "r"(bar), "r"(c0), "r"(c1) : "memory");
}
__device__ __forceinline__ void tma_2d_mc(uint32_t dst, const CUtensorMap* m, int c0, int c1, uint32_t bar, uint16_t mask) {
  asm volatile("cp.async.bulk.tensor.2d.shared::cluster.global.mbarrier::complete_tx::bytes.multicast::cluster [%0], [%1, {%3, %4}], [%2], %5;" ::"r"(dst), "l"(m), "r"(bar), "r"(c0), "r"(c1), "h"(mask) : "memory");
}
__device__ __forceinline__ uint32_t mapa(uint32_t addr, uint32_t rank) { uint32_t r; asm("mapa.shared::cluster.u32 %0, %1, %2;" : "=r"(r) : "r"(addr), "r"(rank)); return r; }
__device__ __forceinline__ uint32_t cluster_rank() { uint32_t r; asm("mov.u32 %0, %%cluster_ctarank;" : "=r"(r)); return r; }
__device__ __forceinline__ void cluster_arrive_relaxed() { asm volatile("barrier.cluster.arrive.relaxed.aligned;" ::: "memory"); }
__device__ __forceinline__ void cluster_wait() { asm volatile("barrier.cluster.wait.acquire.aligned;" ::: "memory"); }
__device__ __forceinline__ bool elect_one() {
  uint32_t pred;
  asm volatile("{\n.reg .pred p;\nelect.sync _|p, 0xffffffff;\nselp.u32 %0, 1, 0, p;\n}\n" : "=r"(pred));
  return pred != 0;
}
__device__ __forceinline__ void pdl_launch() { asm volatile("griddepcontrol.launch_dependents;" ::: "memory"); }
__device__ __forceinline__ void pdl_wait() { asm volatile("griddepcontrol.wait;" ::: "memory"); }
__device__ __forceinline__ void fence_barrier_init() { asm volatile("fence.mbarrier_init.release.cluster;" ::: "memory"); }
__device__ __forceinline__ void fence_proxy_async() { asm volatile("fence.proxy.async.shared::cta;" ::: "memory"); }
__device__ __forceinline__ void prefetch_tmap(const CUtensorMap* m) { asm volatile("prefetch.tensormap [%0];" ::"l"(m) : "memory"); }
__device__ __forceinline__ uint64_t mk_desc(uint32_t addr, uint32_t lbo, uint32_t sbo, uint32_t mode) {
  return (uint64_t)((addr & 0x3FFFF) >> 4) | ((uint64_t)(lbo >> 4) << 16) | ((uint64_t)(sbo >> 4) << 32) | ((uint64_t)mode << 62);
}

__device__ __forceinline__ void wgmma_ssp_n240_t01(float (&d)[120], uint64_t da, uint64_t db, int sd) {
  asm volatile("{\n.reg .pred p;\nsetp.ne.b32 p, %122, 0;\n"
    "wgmma.mma_async.sync.aligned.m64n240k16.f32.bf16.bf16 {%0, %1, %2, %3, %4, %5, %6, %7, %8, %9, %10, %11, %12, %13, %14, %15, %16, %17, %18, %19, %20, %21, %22, %23, %24, %25, %26, %27, %28, %29, %30, %31, %32, %33, %34, %35, %36, %37, %38, %39, %40, %41, %42, %43, %44, %45, %46, %47, %48, %49, %50, %51, %52, %53, %54, %55, %56, %57, %58, %59, %60, %61, %62, %63, %64, %65, %66, %67, %68, %69, %70, %71, %72, %73, %74, %75, %76, %77, %78, %79, %80, %81, %82, %83, %84, %85, %86, %87, %88, %89, %90, %91, %92, %93, %94, %95, %96, %97, %98, %99, %100, %101, %102, %103, %104, %105, %106, %107, %108, %109, %110, %111, %112, %113, %114, %115, %116, %117, %118, %119}, %120, %121, p, 1, 1, 0, 1;\n}\n"
    : "+f"(d[0]), "+f"(d[1]), "+f"(d[2]), "+f"(d[3]), "+f"(d[4]), "+f"(d[5]), "+f"(d[6]), "+f"(d[7]), "+f"(d[8]), "+f"(d[9]), "+f"(d[10]), "+f"(d[11]), "+f"(d[12]), "+f"(d[13]), "+f"(d[14]), "+f"(d[15]), "+f"(d[16]), "+f"(d[17]), "+f"(d[18]), "+f"(d[19]), "+f"(d[20]), "+f"(d[21]), "+f"(d[22]), "+f"(d[23]), "+f"(d[24]), "+f"(d[25]), "+f"(d[26]), "+f"(d[27]), "+f"(d[28]), "+f"(d[29]), "+f"(d[30]), "+f"(d[31]), "+f"(d[32]), "+f"(d[33]), "+f"(d[34]), "+f"(d[35]), "+f"(d[36]), "+f"(d[37]), "+f"(d[38]), "+f"(d[39]), "+f"(d[40]), "+f"(d[41]), "+f"(d[42]), "+f"(d[43]), "+f"(d[44]), "+f"(d[45]), "+f"(d[46]), "+f"(d[47]), "+f"(d[48]), "+f"(d[49]), "+f"(d[50]), "+f"(d[51]), "+f"(d[52]), "+f"(d[53]), "+f"(d[54]), "+f"(d[55]), "+f"(d[56]), "+f"(d[57]), "+f"(d[58]), "+f"(d[59]), "+f"(d[60]), "+f"(d[61]), "+f"(d[62]), "+f"(d[63]), "+f"(d[64]), "+f"(d[65]), "+f"(d[66]), "+f"(d[67]), "+f"(d[68]), "+f"(d[69]), "+f"(d[70]), "+f"(d[71]), "+f"(d[72]), "+f"(d[73]), "+f"(d[74]), "+f"(d[75]), "+f"(d[76]), "+f"(d[77]), "+f"(d[78]), "+f"(d[79]), "+f"(d[80]), "+f"(d[81]), "+f"(d[82]), "+f"(d[83]), "+f"(d[84]), "+f"(d[85]), "+f"(d[86]), "+f"(d[87]), "+f"(d[88]), "+f"(d[89]), "+f"(d[90]), "+f"(d[91]), "+f"(d[92]), "+f"(d[93]), "+f"(d[94]), "+f"(d[95]), "+f"(d[96]), "+f"(d[97]), "+f"(d[98]), "+f"(d[99]), "+f"(d[100]), "+f"(d[101]), "+f"(d[102]), "+f"(d[103]), "+f"(d[104]), "+f"(d[105]), "+f"(d[106]), "+f"(d[107]), "+f"(d[108]), "+f"(d[109]), "+f"(d[110]), "+f"(d[111]), "+f"(d[112]), "+f"(d[113]), "+f"(d[114]), "+f"(d[115]), "+f"(d[116]), "+f"(d[117]), "+f"(d[118]), "+f"(d[119])
    : "l"(da), "l"(db), "r"(sd));
}
__device__ __forceinline__ void wgmma_ssp_n256_t01(float (&d)[128], uint64_t da, uint64_t db, int sd) {
  asm volatile("{\n.reg .pred p;\nsetp.ne.b32 p, %130, 0;\n"
    "wgmma.mma_async.sync.aligned.m64n256k16.f32.bf16.bf16 {%0, %1, %2, %3, %4, %5, %6, %7, %8, %9, %10, %11, %12, %13, %14, %15, %16, %17, %18, %19, %20, %21, %22, %23, %24, %25, %26, %27, %28, %29, %30, %31, %32, %33, %34, %35, %36, %37, %38, %39, %40, %41, %42, %43, %44, %45, %46, %47, %48, %49, %50, %51, %52, %53, %54, %55, %56, %57, %58, %59, %60, %61, %62, %63, %64, %65, %66, %67, %68, %69, %70, %71, %72, %73, %74, %75, %76, %77, %78, %79, %80, %81, %82, %83, %84, %85, %86, %87, %88, %89, %90, %91, %92, %93, %94, %95, %96, %97, %98, %99, %100, %101, %102, %103, %104, %105, %106, %107, %108, %109, %110, %111, %112, %113, %114, %115, %116, %117, %118, %119, %120, %121, %122, %123, %124, %125, %126, %127}, %128, %129, p, 1, 1, 0, 1;\n}\n"
    : "+f"(d[0]), "+f"(d[1]), "+f"(d[2]), "+f"(d[3]), "+f"(d[4]), "+f"(d[5]), "+f"(d[6]), "+f"(d[7]), "+f"(d[8]), "+f"(d[9]), "+f"(d[10]), "+f"(d[11]), "+f"(d[12]), "+f"(d[13]), "+f"(d[14]), "+f"(d[15]), "+f"(d[16]), "+f"(d[17]), "+f"(d[18]), "+f"(d[19]), "+f"(d[20]), "+f"(d[21]), "+f"(d[22]), "+f"(d[23]), "+f"(d[24]), "+f"(d[25]), "+f"(d[26]), "+f"(d[27]), "+f"(d[28]), "+f"(d[29]), "+f"(d[30]), "+f"(d[31]), "+f"(d[32]), "+f"(d[33]), "+f"(d[34]), "+f"(d[35]), "+f"(d[36]), "+f"(d[37]), "+f"(d[38]), "+f"(d[39]), "+f"(d[40]), "+f"(d[41]), "+f"(d[42]), "+f"(d[43]), "+f"(d[44]), "+f"(d[45]), "+f"(d[46]), "+f"(d[47]), "+f"(d[48]), "+f"(d[49]), "+f"(d[50]), "+f"(d[51]), "+f"(d[52]), "+f"(d[53]), "+f"(d[54]), "+f"(d[55]), "+f"(d[56]), "+f"(d[57]), "+f"(d[58]), "+f"(d[59]), "+f"(d[60]), "+f"(d[61]), "+f"(d[62]), "+f"(d[63]), "+f"(d[64]), "+f"(d[65]), "+f"(d[66]), "+f"(d[67]), "+f"(d[68]), "+f"(d[69]), "+f"(d[70]), "+f"(d[71]), "+f"(d[72]), "+f"(d[73]), "+f"(d[74]), "+f"(d[75]), "+f"(d[76]), "+f"(d[77]), "+f"(d[78]), "+f"(d[79]), "+f"(d[80]), "+f"(d[81]), "+f"(d[82]), "+f"(d[83]), "+f"(d[84]), "+f"(d[85]), "+f"(d[86]), "+f"(d[87]), "+f"(d[88]), "+f"(d[89]), "+f"(d[90]), "+f"(d[91]), "+f"(d[92]), "+f"(d[93]), "+f"(d[94]), "+f"(d[95]), "+f"(d[96]), "+f"(d[97]), "+f"(d[98]), "+f"(d[99]), "+f"(d[100]), "+f"(d[101]), "+f"(d[102]), "+f"(d[103]), "+f"(d[104]), "+f"(d[105]), "+f"(d[106]), "+f"(d[107]), "+f"(d[108]), "+f"(d[109]), "+f"(d[110]), "+f"(d[111]), "+f"(d[112]), "+f"(d[113]), "+f"(d[114]), "+f"(d[115]), "+f"(d[116]), "+f"(d[117]), "+f"(d[118]), "+f"(d[119]), "+f"(d[120]), "+f"(d[121]), "+f"(d[122]), "+f"(d[123]), "+f"(d[124]), "+f"(d[125]), "+f"(d[126]), "+f"(d[127])
    : "l"(da), "l"(db), "r"(sd));
}
__device__ __forceinline__ void wgmma_ssp_n192_t01(float (&d)[96], uint64_t da, uint64_t db, int sd) {
  asm volatile("{\n.reg .pred p;\nsetp.ne.b32 p, %98, 0;\n"
    "wgmma.mma_async.sync.aligned.m64n192k16.f32.bf16.bf16 {%0, %1, %2, %3, %4, %5, %6, %7, %8, %9, %10, %11, %12, %13, %14, %15, %16, %17, %18, %19, %20, %21, %22, %23, %24, %25, %26, %27, %28, %29, %30, %31, %32, %33, %34, %35, %36, %37, %38, %39, %40, %41, %42, %43, %44, %45, %46, %47, %48, %49, %50, %51, %52, %53, %54, %55, %56, %57, %58, %59, %60, %61, %62, %63, %64, %65, %66, %67, %68, %69, %70, %71, %72, %73, %74, %75, %76, %77, %78, %79, %80, %81, %82, %83, %84, %85, %86, %87, %88, %89, %90, %91, %92, %93, %94, %95}, %96, %97, p, 1, 1, 0, 1;\n}\n"
    : "+f"(d[0]), "+f"(d[1]), "+f"(d[2]), "+f"(d[3]), "+f"(d[4]), "+f"(d[5]), "+f"(d[6]), "+f"(d[7]), "+f"(d[8]), "+f"(d[9]), "+f"(d[10]), "+f"(d[11]), "+f"(d[12]), "+f"(d[13]), "+f"(d[14]), "+f"(d[15]), "+f"(d[16]), "+f"(d[17]), "+f"(d[18]), "+f"(d[19]), "+f"(d[20]), "+f"(d[21]), "+f"(d[22]), "+f"(d[23]), "+f"(d[24]), "+f"(d[25]), "+f"(d[26]), "+f"(d[27]), "+f"(d[28]), "+f"(d[29]), "+f"(d[30]), "+f"(d[31]), "+f"(d[32]), "+f"(d[33]), "+f"(d[34]), "+f"(d[35]), "+f"(d[36]), "+f"(d[37]), "+f"(d[38]), "+f"(d[39]), "+f"(d[40]), "+f"(d[41]), "+f"(d[42]), "+f"(d[43]), "+f"(d[44]), "+f"(d[45]), "+f"(d[46]), "+f"(d[47]), "+f"(d[48]), "+f"(d[49]), "+f"(d[50]), "+f"(d[51]), "+f"(d[52]), "+f"(d[53]), "+f"(d[54]), "+f"(d[55]), "+f"(d[56]), "+f"(d[57]), "+f"(d[58]), "+f"(d[59]), "+f"(d[60]), "+f"(d[61]), "+f"(d[62]), "+f"(d[63]), "+f"(d[64]), "+f"(d[65]), "+f"(d[66]), "+f"(d[67]), "+f"(d[68]), "+f"(d[69]), "+f"(d[70]), "+f"(d[71]), "+f"(d[72]), "+f"(d[73]), "+f"(d[74]), "+f"(d[75]), "+f"(d[76]), "+f"(d[77]), "+f"(d[78]), "+f"(d[79]), "+f"(d[80]), "+f"(d[81]), "+f"(d[82]), "+f"(d[83]), "+f"(d[84]), "+f"(d[85]), "+f"(d[86]), "+f"(d[87]), "+f"(d[88]), "+f"(d[89]), "+f"(d[90]), "+f"(d[91]), "+f"(d[92]), "+f"(d[93]), "+f"(d[94]), "+f"(d[95])
    : "l"(da), "l"(db), "r"(sd));
}
__device__ __forceinline__ void wgmma_ssp_n128_t01(float (&d)[64], uint64_t da, uint64_t db, int sd) {
  asm volatile("{\n.reg .pred p;\nsetp.ne.b32 p, %66, 0;\n"
    "wgmma.mma_async.sync.aligned.m64n128k16.f32.bf16.bf16 {%0, %1, %2, %3, %4, %5, %6, %7, %8, %9, %10, %11, %12, %13, %14, %15, %16, %17, %18, %19, %20, %21, %22, %23, %24, %25, %26, %27, %28, %29, %30, %31, %32, %33, %34, %35, %36, %37, %38, %39, %40, %41, %42, %43, %44, %45, %46, %47, %48, %49, %50, %51, %52, %53, %54, %55, %56, %57, %58, %59, %60, %61, %62, %63}, %64, %65, p, 1, 1, 0, 1;\n}\n"
    : "+f"(d[0]), "+f"(d[1]), "+f"(d[2]), "+f"(d[3]), "+f"(d[4]), "+f"(d[5]), "+f"(d[6]), "+f"(d[7]), "+f"(d[8]), "+f"(d[9]), "+f"(d[10]), "+f"(d[11]), "+f"(d[12]), "+f"(d[13]), "+f"(d[14]), "+f"(d[15]), "+f"(d[16]), "+f"(d[17]), "+f"(d[18]), "+f"(d[19]), "+f"(d[20]), "+f"(d[21]), "+f"(d[22]), "+f"(d[23]), "+f"(d[24]), "+f"(d[25]), "+f"(d[26]), "+f"(d[27]), "+f"(d[28]), "+f"(d[29]), "+f"(d[30]), "+f"(d[31]), "+f"(d[32]), "+f"(d[33]), "+f"(d[34]), "+f"(d[35]), "+f"(d[36]), "+f"(d[37]), "+f"(d[38]), "+f"(d[39]), "+f"(d[40]), "+f"(d[41]), "+f"(d[42]), "+f"(d[43]), "+f"(d[44]), "+f"(d[45]), "+f"(d[46]), "+f"(d[47]), "+f"(d[48]), "+f"(d[49]), "+f"(d[50]), "+f"(d[51]), "+f"(d[52]), "+f"(d[53]), "+f"(d[54]), "+f"(d[55]), "+f"(d[56]), "+f"(d[57]), "+f"(d[58]), "+f"(d[59]), "+f"(d[60]), "+f"(d[61]), "+f"(d[62]), "+f"(d[63])
    : "l"(da), "l"(db), "r"(sd));
}
__device__ __forceinline__ void wgmma_ssp_n32_t01(float (&d)[16], uint64_t da, uint64_t db, int sd) {
  asm volatile("{\n.reg .pred p;\nsetp.ne.b32 p, %18, 0;\n"
    "wgmma.mma_async.sync.aligned.m64n32k16.f32.bf16.bf16 {%0, %1, %2, %3, %4, %5, %6, %7, %8, %9, %10, %11, %12, %13, %14, %15}, %16, %17, p, 1, 1, 0, 1;\n}\n"
    : "+f"(d[0]), "+f"(d[1]), "+f"(d[2]), "+f"(d[3]), "+f"(d[4]), "+f"(d[5]), "+f"(d[6]), "+f"(d[7]), "+f"(d[8]), "+f"(d[9]), "+f"(d[10]), "+f"(d[11]), "+f"(d[12]), "+f"(d[13]), "+f"(d[14]), "+f"(d[15])
    : "l"(da), "l"(db), "r"(sd));
}
__device__ __forceinline__ void wgmma_ss_n64_t00(float (&d)[32], uint64_t da, uint64_t db) {
  asm volatile("{\n.reg .pred p;\nsetp.ne.b32 p, 1, 0;\n"
    "wgmma.mma_async.sync.aligned.m64n64k16.f32.bf16.bf16 {%0, %1, %2, %3, %4, %5, %6, %7, %8, %9, %10, %11, %12, %13, %14, %15, %16, %17, %18, %19, %20, %21, %22, %23, %24, %25, %26, %27, %28, %29, %30, %31}, %32, %33, p, 1, 1, 0, 0;\n}\n"
    : "+f"(d[0]), "+f"(d[1]), "+f"(d[2]), "+f"(d[3]), "+f"(d[4]), "+f"(d[5]), "+f"(d[6]), "+f"(d[7]), "+f"(d[8]), "+f"(d[9]), "+f"(d[10]), "+f"(d[11]), "+f"(d[12]), "+f"(d[13]), "+f"(d[14]), "+f"(d[15]), "+f"(d[16]), "+f"(d[17]), "+f"(d[18]), "+f"(d[19]), "+f"(d[20]), "+f"(d[21]), "+f"(d[22]), "+f"(d[23]), "+f"(d[24]), "+f"(d[25]), "+f"(d[26]), "+f"(d[27]), "+f"(d[28]), "+f"(d[29]), "+f"(d[30]), "+f"(d[31])
    : "l"(da), "l"(db));
}
__device__ __forceinline__ void wgmma_ss0_n64_t00(float (&d)[32], uint64_t da, uint64_t db) {
  asm volatile("{\n.reg .pred p;\nsetp.ne.b32 p, 0, 0;\n"
    "wgmma.mma_async.sync.aligned.m64n64k16.f32.bf16.bf16 {%0, %1, %2, %3, %4, %5, %6, %7, %8, %9, %10, %11, %12, %13, %14, %15, %16, %17, %18, %19, %20, %21, %22, %23, %24, %25, %26, %27, %28, %29, %30, %31}, %32, %33, p, 1, 1, 0, 0;\n}\n"
    : "=f"(d[0]), "=f"(d[1]), "=f"(d[2]), "=f"(d[3]), "=f"(d[4]), "=f"(d[5]), "=f"(d[6]), "=f"(d[7]), "=f"(d[8]), "=f"(d[9]), "=f"(d[10]), "=f"(d[11]), "=f"(d[12]), "=f"(d[13]), "=f"(d[14]), "=f"(d[15]), "=f"(d[16]), "=f"(d[17]), "=f"(d[18]), "=f"(d[19]), "=f"(d[20]), "=f"(d[21]), "=f"(d[22]), "=f"(d[23]), "=f"(d[24]), "=f"(d[25]), "=f"(d[26]), "=f"(d[27]), "=f"(d[28]), "=f"(d[29]), "=f"(d[30]), "=f"(d[31])
    : "l"(da), "l"(db));
}
__device__ __forceinline__ void wgmma_rs_n24_t1(float (&d)[12], uint32_t a0, uint32_t a1, uint32_t a2, uint32_t a3, uint64_t db, int sd) {
  asm volatile("{\n.reg .pred p;\nsetp.ne.b32 p, %17, 0;\n"
    "wgmma.mma_async.sync.aligned.m64n24k16.f32.bf16.bf16 {%0, %1, %2, %3, %4, %5, %6, %7, %8, %9, %10, %11}, {%12, %13, %14, %15}, %16, p, 1, 1, 1;\n}\n"
    : "+f"(d[0]), "+f"(d[1]), "+f"(d[2]), "+f"(d[3]), "+f"(d[4]), "+f"(d[5]), "+f"(d[6]), "+f"(d[7]), "+f"(d[8]), "+f"(d[9]), "+f"(d[10]), "+f"(d[11])
    : "r"(a0), "r"(a1), "r"(a2), "r"(a3), "l"(db), "r"(sd));
}

__device__ __forceinline__ uint4 quad_transpose(uint32_t x0, uint32_t x1, uint32_t x2, uint32_t x3, bool odd, bool hi) {
  const uint32_t ra = __shfl_xor_sync(0xffffffffu, odd ? x0 : x1, 1), rb = __shfl_xor_sync(0xffffffffu, odd ? x2 : x3, 1);
  const uint32_t a0 = odd ? ra : x0, a1 = odd ? x1 : ra, b0 = odd ? rb : x2, b1 = odd ? x3 : rb;
  const uint32_t r0 = __shfl_xor_sync(0xffffffffu, hi ? a0 : b0, 2), r1 = __shfl_xor_sync(0xffffffffu, hi ? a1 : b1, 2);
  return hi ? make_uint4(r0, r1, b0, b1) : make_uint4(a0, a1, r0, r1);
}

constexpr int K1_NST = 4;
constexpr int NPROD = 2;
constexpr uint32_t PF0 = 128;
constexpr int K1_A_BYTES = 10 * 16384;
constexpr int K1_SMEM = K1_A_BYTES + K1_NST * 16384 + 1024 + 1024;

template <int BN, bool UNROLL, typename MMA, typename SIDE>
__device__ __forceinline__ void k1_mainloop(float (&acc)[BN / 2], MMA mma, SIDE side, uint32_t sA, uint32_t sB, uint32_t barA, uint32_t barF,
                                            uint32_t barE, uint32_t barE_peer, int it0, bool waitA, int wgi, bool elect) {
  const uint64_t dA0 = mk_desc(sA + wgi * 8192, 16, 1024, 1);
  const uint64_t dB0 = mk_desc(sB, 4096, 1024, 1);
  fence_regs(acc);
#pragma unroll(UNROLL ? 20 : 1)
  for (int s = 0; s < 20; s++) {
    const int it = it0 + s, st = it & (K1_NST - 1);
    if (waitA && !(s & 1)) mbar_wait(barA + 8 * (s >> 1), 0);
    mbar_wait(barF + 8 * st, (it / K1_NST) & 1);
    const uint64_t da = dA0 + (uint32_t)((s >> 1) * 1024 + (s & 1) * 4);
    const uint64_t db = dB0 + (uint32_t)(st * 1024);
    wg_fence();
    mma(acc, da, db, s);
    mma(acc, da + 2, db + 128, 1);
    wg_commit();
    side(s);
    if (s > 0) {
      wg_wait<1>();
      if (elect && it <= 40 - K1_NST) { const int ps = (it - 1) & (K1_NST - 1); mbar_arrive_cluster(barE + 8 * ps); mbar_arrive_cluster(barE_peer + 8 * ps); }
    }
  }
  wg_wait<0>();
  fence_regs(acc);
  if (elect && it0 == 0) { const int ps = (it0 + 19) & (K1_NST - 1); mbar_arrive_cluster(barE + 8 * ps); mbar_arrive_cluster(barE_peer + 8 * ps); }
}

__device__ __forceinline__ void st32(uint8_t* p, uint32_t v) { *reinterpret_cast<uint32_t*>(p) = v; }

__device__ __forceinline__ void k1_qkv_pack(const float (&acc)[120], uint32_t (&pk)[60], int slot0) {
#pragma unroll
  for (int j = 0; j < 30; j++) {
    const float sc = slot0 + 2 * (j / 5) < 32 ? 0.32259642f : 1.0f;
    pk[2 * j] = pack_bf16(acc[4 * j] * sc, acc[4 * j + 1] * sc);
    pk[2 * j + 1] = pack_bf16(acc[4 * j + 2] * sc, acc[4 * j + 3] * sc);
  }
}
__device__ __forceinline__ float sq2(uint32_t w) { const float a = bf_lo(w), b = bf_hi(w); return fmaf(a, a, b * b); }
__device__ __forceinline__ void k1_qkv_store(const uint32_t (&pk)[60], int hp, int part, int slot0, int grp, int g, int t4, int lane) {
  const int slot = slot0 + 2 * hp, which = slot >> 5, head = slot & 31;
  const uint32_t gs = which == 0 ? 512u : 768u, hs = which == 0 ? 131072u : 196608u;
  uint8_t* p0 = g_QKV + (head * hs + grp * gs + g * 16 + (which == 0 ? 0u : (which == 1 ? KV_OFF : KV_OFF + 384u)));
  const bool lo2 = t4 < 2, odd = t4 & 1;
  const uint32_t* w = pk + hp * 10;
  const uint32_t e01 = (odd ? 128u : 0u) + (lo2 ? 0u : gs);
  if (part == 0) {
    *reinterpret_cast<uint4*>(p0 + e01) = quad_transpose(w[0], w[2], w[1], w[3], odd, !lo2);
    uint32_t na = 0, nb = 0;
#pragma unroll
    for (int r = 0; r < 2; r++) {
      const float m = sq2(w[4 + r]);
      float a = sq2(w[r]) + sq2(w[2 + r]) + (lo2 ? m : 0.f), b = sq2(w[6 + r]) + sq2(w[8 + r]) + (lo2 ? 0.f : m);
      a += __shfl_xor_sync(0xffffffffu, a, 1); b += __shfl_xor_sync(0xffffffffu, b, 1);
      a += __shfl_xor_sync(0xffffffffu, a, 2); b += __shfl_xor_sync(0xffffffffu, b, 2);
      na = max(na, __float_as_uint(a)); nb = max(nb, __float_as_uint(b));
    }
    na = __reduce_max_sync(0xffffffffu, na);
    nb = __reduce_max_sync(0xffffffffu, nb);
    if (lane < 2) g_norm[(slot + lane) * 128 + (grp >> 1)] = __uint_as_float(lane ? nb : na);
  } else if (part == 1) {
    const uint4 o4 = quad_transpose(lo2 ? w[6] : w[4], lo2 ? w[8] : w[6], lo2 ? w[7] : w[5], lo2 ? w[9] : w[7], odd, !lo2);
    *reinterpret_cast<uint4*>(p0 + hs + e01) = make_uint4(o4.z, o4.w, o4.x, o4.y);
  } else {
    uint2 cp;
    if (which == 0) cp = make_uint2(0x42FB47C0u, 0x0000BDCCu);
    else if (which == 1) cp = ((MUFU_MASK >> ((grp + (odd ? 1 : 0)) & 15)) & 1) ? make_uint2(0u, 0u) : make_uint2(0x3F803F80u, 0x00003F80u);
    else cp = make_uint2(0x00003F80u, 0u);
    const uint32_t e2 = (lo2 ? 0u : hs) + 256u + (odd ? gs : 0u);
    const uint32_t u0 = lo2 ? w[4] : w[8], u1 = lo2 ? w[5] : w[9];
    const uint32_t ur = __shfl_xor_sync(0xffffffffu, odd ? u0 : u1, 1);
    *reinterpret_cast<uint4*>(p0 + e2) = make_uint4(odd ? ur : u0, odd ? u1 : ur, cp.x, cp.y);
    if (which == 0) *reinterpret_cast<uint4*>(p0 + e2 + 128) = make_uint4(0, 0, 0, 0);
  }
}

__global__ void __cluster_dims__(2, 1, 1) __launch_bounds__(384, 1)
k1_proj(const __grid_constant__ CUtensorMap tmX, const __grid_constant__ CUtensorMap tmWqkv, const __grid_constant__ CUtensorMap tmW1,
        const __nv_bfloat16* __restrict__ b1, const __nv_bfloat16* __restrict__ gate_w,
        const uint8_t* __restrict__ wqkv, const uint8_t* __restrict__ w1, const uint8_t* __restrict__ w2, const uint8_t* __restrict__ wo) {
  extern __shared__ uint8_t smem_raw[];
  const uint32_t sb = (smem_u32(smem_raw) + 1023u) & ~1023u;
  const uint32_t sA = sb, sB = sb + K1_A_BYTES, bars = sB + K1_NST * 16384;
  const uint32_t barA = bars, barF = bars + 80, barE = barF + 8 * K1_NST;
  const int tid = threadIdx.x, lane = tid & 31;
  const int warp = __shfl_sync(0xffffffffu, tid >> 5, 0);
  const int rb = blockIdx.x & 15, cg = blockIdx.x >> 4;
  const uint32_t rank = cluster_rank();
  const bool fwide = (0xA8 >> cg) & 1;
  const int fcol = (cg * 3 + __popc(0xA8 & ((1 << cg) - 1))) * 64;
  if (tid == 0) {
    prefetch_tmap(&tmX); prefetch_tmap(&tmWqkv); prefetch_tmap(&tmW1);
    for (int i = 0; i < 10; i++) mbar_init(barA + 8 * i, 1);
    for (int i = 0; i < K1_NST; i++) { mbar_init(barF + 8 * i, 1); mbar_init(barE + 8 * i, 16); }
    fence_barrier_init();
    fence_proxy_async();
    for (int i = 0; i < 4; i++) { mbar_expect_tx(barA + 8 * i, 16384); mbar_expect_tx(barF + 8 * i, 16384); }
    tma_2d(sA, &tmX, 0, rb * 128, barA);
    for (int b = 0; b < 4; b++) tma_2d(sB + b * 4096, &tmWqkv, cg * 240 + b * 64, 0, barF);
  }
  __syncthreads();
  if (lane == 0) {
    const int i = 1 + (warp >> 2), b = warp & 3;
    tma_2d(sB + i * 16384 + b * 4096, &tmWqkv, cg * 240 + b * 64, i * 32, barF + 8 * i);
    if (b == 3) tma_2d(sA + i * 16384, &tmX, i * 64, rb * 128, barA + 8 * i);
  }
  pdl_launch();
  __syncwarp();
  cluster_arrive_relaxed();
  cluster_wait();

  if (warp < 4) {
    asm volatile("setmaxnreg.dec.sync.aligned.u32 40;");
    if (warp == 0 || warp == 2) {
      if (lane == 0) {
#pragma unroll 1
        for (int it = K1_NST + (warp >> 1); it < 40; it += NPROD) {
          const int st = it & (K1_NST - 1);
          const bool t0 = it < 20;
          const CUtensorMap* m = t0 ? &tmWqkv : &tmW1;
          const int col = (t0 ? cg * 240 : fcol) + (int)rank * 128;
          const bool full = t0 || fwide;
          const int k = (t0 ? it : it - 20) * 32;
          const uint32_t dst = sB + st * 16384 + rank * 8192;
          mbar_wait(barE + 8 * st, ((it / K1_NST) - 1) & 1);
          mbar_expect_tx(barF + 8 * st, full ? 16384 : 12288);
          tma_2d_mc(dst, m, col, k, barF + 8 * st, (uint16_t)3);
          if (full || rank == 0) tma_2d_mc(dst + 4096, m, col + 64, k, barF + 8 * st, (uint16_t)3);
          if (it < 10) {
            const int ka = it;
            mbar_expect_tx(barA + 8 * ka, 16384);
            tma_2d(sA + ka * 16384, &tmX, ka * 64, rb * 128, barA + 8 * ka);
          }
        }
      }
    } else if (warp == 3) {
      if (lane == 0) {
        const uint32_t b = blockIdx.x;
        l2_prefetch(wqkv + PF0 * 3840u + b * ((640u - PF0) * 30u), (640u - PF0) * 30u);
        mbar_wait(barA + 8 * 3, 0);
        l2_prefetch(w1 + b * 17280u, 17280u);
        mbar_wait(barA + 8 * 9, 0);
        l2_prefetch(w2 + b * 17280u, 17280u);
        l2_prefetch(wo + b * 6400u, 6400u);
      }
    } else if (warp == 1) {
      const int r = cg * 16 + (lane >> 1), half = lane & 1;
      float acc = 0.f;
      mbar_wait(barA + 72, 0);
#pragma unroll 1
      for (int kb = half * 5; kb < half * 5 + 5; kb++) {
        mbar_wait(barA + 8 * kb, 0);
#pragma unroll
        for (int c = 0; c < 8; c++) {
          uint4 xv;
          asm volatile("ld.shared.v4.u32 {%0,%1,%2,%3}, [%4];" : "=r"(xv.x), "=r"(xv.y), "=r"(xv.z), "=r"(xv.w)
                       : "r"(sA + kb * 16384 + r * 128 + ((c ^ (r & 7)) << 4)));
          const uint4 wv = __ldg(reinterpret_cast<const uint4*>(gate_w + kb * 64 + c * 8));
          acc = fmaf(bf_lo(xv.x), bf_lo(wv.x), acc); acc = fmaf(bf_hi(xv.x), bf_hi(wv.x), acc);
          acc = fmaf(bf_lo(xv.y), bf_lo(wv.y), acc); acc = fmaf(bf_hi(xv.y), bf_hi(wv.y), acc);
          acc = fmaf(bf_lo(xv.z), bf_lo(wv.z), acc); acc = fmaf(bf_hi(xv.z), bf_hi(wv.z), acc);
          acc = fmaf(bf_lo(xv.w), bf_lo(wv.w), acc); acc = fmaf(bf_hi(xv.w), bf_hi(wv.w), acc);
        }
      }
      acc += __shfl_xor_sync(0xffffffffu, acc, 1);
      if (!half) g_gate[rb * 128 + r] = 1.f / (1.f + __expf(-acc));
    }
  } else {
    const int wgi = (warp >> 2) - 1, wq = warp & 3, g = lane >> 2, t4 = lane & 3;
    const uint32_t barE_self = mapa(barE, rank), barE_peer = mapa(barE, rank ^ 1);
    const bool elect = lane == 0;
    asm volatile("setmaxnreg.inc.sync.aligned.u32 232;");
    uint32_t pk[60];
    const int grp = rb * 16 + wgi * 8 + wq * 2, slot0 = cg * 12;
    {
      float acc[120];
      k1_mainloop<240, false>(acc, [](float (&d)[120], uint64_t a, uint64_t b, int sd) { wgmma_ssp_n240_t01(d, a, b, sd); }, [](int) {},
                              sA, sB, barA, barF, barE_self, barE_peer, 0, true, wgi, elect);
      k1_qkv_pack(acc, pk, slot0);
    }
    auto ffn = [&](auto nc, auto mma) {
      constexpr int N = decltype(nc)::value;
      float acc[N / 2];
      uint32_t bias[N / 8];
      const uint32_t* bp = reinterpret_cast<const uint32_t*>(b1 + fcol + t4 * 2);
#pragma unroll
      for (int j = 0; j < N / 8; j++) bias[j] = __ldg(bp + j * 4);
      k1_mainloop<N, true>(acc, mma, [&](int s) { if (s < 18) k1_qkv_store(pk, s / 3, s % 3, slot0, grp, g, t4, lane); },
                           sA, sB, barA, barF, barE_self, barE_peer, 20, false, wgi, elect);
      uint8_t* base = g_A2 + ((size_t)(rb * 296 + (fcol >> 3)) * 16 + wgi * 8 + wq * 2) * 128 + g * 16 + t4 * 4;
#pragma unroll
      for (int j = 0; j < N / 8; j++) {
        const float c0 = bf_lo(bias[j]), c1 = bf_hi(bias[j]);
        const float h0 = fmaxf(acc[4 * j] + c0, 0.f), h1 = fmaxf(acc[4 * j + 1] + c1, 0.f);
        const float h2 = fmaxf(acc[4 * j + 2] + c0, 0.f), h3 = fmaxf(acc[4 * j + 3] + c1, 0.f);
        st32(base + j * 2048, pack_bf16(h0 * h0, h1 * h1));
        st32(base + j * 2048 + 128, pack_bf16(h2 * h2, h3 * h3));
      }
    };
    if (fwide) ffn(std::integral_constant<int, 256>{}, [](float (&d)[128], uint64_t a, uint64_t b, int sd) { wgmma_ssp_n256_t01(d, a, b, sd); });
    else ffn(std::integral_constant<int, 192>{}, [](float (&d)[96], uint64_t a, uint64_t b, int sd) { wgmma_ssp_n192_t01(d, a, b, sd); });
  }
}

constexpr int KV_HEAD_BYTES = 256 * 768, Q_BYTES = 8 * 4096;
constexpr int AT_NCHUNK = 16, AT_CHUNK_BYTES = KV_HEAD_BYTES / AT_NCHUNK;
constexpr int AT_SMEM = KV_HEAD_BYTES + Q_BYTES + 1024 + 1024;

template <int T0, int T1, int TOFF>
__device__ __forceinline__ void exp_tiles(const float (&s)[32], uint32_t (&p)[16], uint32_t cmask, uint32_t cone) {
#pragma unroll
  for (int t = T0; t < T1; t++) {
#pragma unroll
    for (int h = 0; h < 2; h++) {
      const float x0 = s[4 * t + 2 * h], x1 = s[4 * t + 2 * h + 1];
      uint32_t r;
      if ((MUFU_MASK >> ((t + TOFF) & 15)) & 1) {
        r = pack_bf16(ex2(x0), ex2(x1));
      } else {
        const uint32_t u = __byte_perm(__float_as_uint(x0), __float_as_uint(x1), 0x5410);
        uint32_t g;
        asm("lop3.b32 %0, %1, %2, %3, 0xEA;" : "=r"(g) : "r"(u), "r"(cmask), "r"(cone));
        r = hfma2_bf16(g, g, 0x40034003u) + u - g;
      }
      p[2 * t + h] = r;
      asm volatile("" : "+r"(p[2 * t + h])::"memory");
    }
  }
}
template <int TOFF>
__device__ __forceinline__ void exp_pv(const float (&s)[32], uint32_t (&p)[16], float (&o)[12], uint64_t dv, int sd, uint32_t cmask, uint32_t cone) {
  exp_tiles<0, 4, TOFF>(s, p, cmask, cone);
  wg_fence();
  wgmma_rs_n24_t1(o, p[0], p[1], p[2], p[3], dv, sd);
  wgmma_rs_n24_t1(o, p[4], p[5], p[6], p[7], dv + 96, 1);
  exp_tiles<4, 8, TOFF>(s, p, cmask, cone);
  wg_fence();
  wgmma_rs_n24_t1(o, p[8], p[9], p[10], p[11], dv + 192, 1);
  wgmma_rs_n24_t1(o, p[12], p[13], p[14], p[15], dv + 288, 1);
}
__device__ __forceinline__ void qk64(float (&s)[32], uint64_t dq, uint64_t dk) {
  wgmma_ss0_n64_t00(s, dq, dk);
  wgmma_ss_n64_t00(s, dq + 16, dk + 16);
}
__device__ __forceinline__ void attn_store(const float (&o)[12], int row0, int head, int lane, float g0, float g1) {
  const int t4 = lane & 3;
  const float l0 = __shfl_sync(0xffffffffu, o[8], (lane & ~3) | 2), l1 = __shfl_sync(0xffffffffu, o[10], (lane & ~3) | 2);
  const float r0 = __fdividef(g0, l0), r1 = __fdividef(g1, l1);
  uint8_t* base = g_A2 + ((size_t)((row0 >> 7) * 296 + 216) * 16 + ((row0 & 127) >> 3)) * 128 + (row0 & 7) * 16;
#pragma unroll
  for (int tt = 0; tt < 3; tt++) {
    const int d = tt * 8 + 2 * t4;
    if (d < 20) {
      const int col = head * 20 + d;
      uint8_t* ptr = base + (col >> 3) * 2048 + (col & 7) * 2;
      *reinterpret_cast<uint32_t*>(ptr) = pack_bf16(o[4 * tt] * r0, o[4 * tt + 1] * r0);
      *reinterpret_cast<uint32_t*>(ptr + 128) = pack_bf16(o[4 * tt + 2] * r1, o[4 * tt + 3] * r1);
    }
  }
}

__device__ __forceinline__ void attn_slow(uint32_t sb, uint32_t bb, int wg, int rowbase, int head, int lane) {
  const uint64_t dk0 = mk_desc(sb, 128, 768, 0), dv0 = mk_desc(sb + 384, 768, 128, 0);
  const uint64_t dq0 = mk_desc(sb + KV_HEAD_BYTES + wg * 8192, 128, 512, 0);
#pragma unroll 1
  for (int mt = 0; mt < 2; mt++) {
    float o[12], s[32];
    uint32_t p[16];
#pragma unroll
    for (int i = 0; i < 12; i++) o[i] = 0.f;
    float m0 = -INFINITY, m1 = -INFINITY;
#pragma unroll 1
    for (int b = 0; b < 32; b++) {
      if (mt == 0 && !(b & 1)) mbar_wait(bb + 8 * (b >> 1), 0);
      wg_fence();
      qk64(s, dq0 + (uint32_t)(mt * 256), dk0 + (uint32_t)(b * 384));
      wg_commit();
      wg_wait<0>();
      fence_regs(s);
      float n0 = m0, n1 = m1;
#pragma unroll
      for (int t = 0; t < 8; t++) { n0 = fmaxf(n0, fmaxf(s[4 * t], s[4 * t + 1])); n1 = fmaxf(n1, fmaxf(s[4 * t + 2], s[4 * t + 3])); }
      n0 = fmaxf(n0, __shfl_xor_sync(0xffffffffu, n0, 1)); n0 = fmaxf(n0, __shfl_xor_sync(0xffffffffu, n0, 2));
      n1 = fmaxf(n1, __shfl_xor_sync(0xffffffffu, n1, 1)); n1 = fmaxf(n1, __shfl_xor_sync(0xffffffffu, n1, 2));
      const float a0 = ex2(m0 - n0), a1 = ex2(m1 - n1);
      m0 = n0; m1 = n1;
#pragma unroll
      for (int t = 0; t < 3; t++) { o[4 * t] *= a0; o[4 * t + 1] *= a0; o[4 * t + 2] *= a1; o[4 * t + 3] *= a1; }
#pragma unroll
      for (int t = 0; t < 8; t++) {
        p[2 * t] = pack_bf16(ex2(s[4 * t] - m0), ex2(s[4 * t + 1] - m0));
        p[2 * t + 1] = pack_bf16(ex2(s[4 * t + 2] - m1), ex2(s[4 * t + 3] - m1));
      }
      fence_regs(o);
      wg_fence();
#pragma unroll
      for (int k = 0; k < 4; k++) wgmma_rs_n24_t1(o, p[4 * k], p[4 * k + 1], p[4 * k + 2], p[4 * k + 3], dv0 + (uint32_t)(b * 384 + k * 96), 1);
      wg_commit();
      wg_wait<0>();
      fence_regs(o);
    }
    attn_store(o, rowbase + mt * 64, head, lane, g_gate[rowbase + mt * 64], g_gate[rowbase + mt * 64 + 8]);
  }
}

__global__ void __launch_bounds__(512, 1) k2_attn(int opaque_zero) {
  extern __shared__ uint8_t smem_raw[];
  const uint32_t sb = (smem_u32(smem_raw) + 1023u) & ~1023u;
  const uint32_t bb = sb + KV_HEAD_BYTES + Q_BYTES;
  const int tid = threadIdx.x, lane = tid & 31;
  const int warp = __shfl_sync(0xffffffffu, tid >> 5, 0), wg = warp >> 2;
  const int head = blockIdx.x >> 2, qb = blockIdx.x & 3;
  if (tid == 0) {
    for (int i = 0; i <= AT_NCHUNK; i++) mbar_init(bb + 8 * i, 1);
    fence_barrier_init();
    fence_proxy_async();
  }
  __syncthreads();
  pdl_wait();
  pdl_launch();
  if (warp < 3 && elect_one()) {
    if (warp == 2) {
      mbar_expect_tx(bb + 8 * AT_NCHUNK, Q_BYTES);
      bulk_g2s(sb + KV_HEAD_BYTES, g_QKV + (size_t)blockIdx.x * Q_BYTES, Q_BYTES, bb + 8 * AT_NCHUNK);
    } else {
      for (int i = warp; i < AT_NCHUNK; i += 2) {
        mbar_expect_tx(bb + 8 * i, AT_CHUNK_BYTES);
        bulk_g2s(sb + i * AT_CHUNK_BYTES, g_QKV + KV_OFF + (size_t)head * KV_HEAD_BYTES + i * AT_CHUNK_BYTES, AT_CHUNK_BYTES, bb + 8 * i);
      }
    }
  }
  __syncwarp();
  bool fast;
  {
    const uint32_t* nb = reinterpret_cast<const uint32_t*>(g_norm);
    const uint4 k4 = *reinterpret_cast<const uint4*>(nb + (32 + head) * 128 + lane * 4);
    const uint4 v4 = *reinterpret_cast<const uint4*>(nb + (64 + head) * 128 + lane * 4);
    const float nq = __uint_as_float(__reduce_max_sync(0xffffffffu, nb[head * 128 + qb * 32 + lane]));
    const float nk = __uint_as_float(__reduce_max_sync(0xffffffffu, max(max(k4.x, k4.y), max(k4.z, k4.w))));
    const float nv = __uint_as_float(__reduce_max_sync(0xffffffffu, max(max(v4.x, v4.y), max(v4.z, v4.w))));
    fast = (nq * nk <= 3364.0f) && (nq <= 1e30f) && (nk <= 1e30f) && (nv <= 1e30f) && (nv >= 1e-18f);
  }
  const int rowbase = qb * 512 + wg * 128 + (warp & 3) * 16 + (lane >> 2);
  mbar_wait(bb + 8 * AT_NCHUNK, 0);
  if (!fast) {
    *reinterpret_cast<uint2*>(smem_raw + (sb - smem_u32(smem_raw)) + KV_HEAD_BYTES + (tid >> 3) * 512 + 256 + (tid & 7) * 16 + 8) = make_uint2(0u, 0u);
    fence_proxy_async();
    __syncthreads();
    attn_slow(sb, bb, wg, rowbase, head, lane);
    return;
  }
  uint32_t cmask = 0x007F007Fu + opaque_zero, cone = 0x3F803F80u + opaque_zero;
  const uint64_t dk0 = mk_desc(sb, 128, 768, 0), dv0 = mk_desc(sb + 384, 768, 128, 0);
  const uint64_t dq0 = mk_desc(sb + KV_HEAD_BYTES + wg * 8192, 128, 512, 0);
  float o[12], s0[32], s1[32];
  uint32_t p0[16], p1[16];
#pragma unroll
  for (int i = 0; i < 12; i++) o[i] = 0.f;
  mbar_wait(bb, 0);
#pragma unroll 1
  for (int mt = 0; mt < 2; mt++) {
    const uint64_t dq = dq0 + (uint32_t)(mt * 256);
    uint64_t dk = dk0, dv = dv0;
    uint32_t bw = bb + 8;
    const float g0 = g_gate[rowbase + mt * 64], g1 = g_gate[rowbase + mt * 64 + 8];
    fence_regs(o);
    wg_fence();
    qk64(s0, dq, dk);
    wg_commit();
    wg_wait<0>();
    fence_regs(s0);
#pragma unroll 1
    for (int c = 0; c < 16; c++) {
      wg_fence();
      qk64(s1, dq, dk + 384);
      wg_commit();
      exp_pv<0>(s0, p0, o, dv, c, cmask, cone);
      wg_commit();
      wg_wait<1>();
      fence_regs(s1);
      if (mt == 0) { mbar_wait(bw, 0); bw += 8; }
      dk += 768;
      wg_fence();
      qk64(s0, dq, dk);
      wg_commit();
      exp_pv<8>(s1, p1, o, dv + 384, 1, cmask, cone);
      wg_commit();
      dv += 768;
      wg_wait<0>();
      fence_regs(s0);
      fence_regs(o);
    }
    attn_store(o, rowbase + mt * 64, head, lane, g0, g1);
  }
}

constexpr int K3_NST = 8, K3_STAGE = 8192 + 10240;
constexpr int K3_RED = 128 * 80 * 4;
constexpr int K3_SMEM = K3_NST * K3_STAGE + K3_RED + 1024 + 1024;

__global__ void __cluster_dims__(2, 1, 1) __launch_bounds__(320, 1)
k3_out(const __grid_constant__ CUtensorMap tmW2, const __grid_constant__ CUtensorMap tmWo, const __grid_constant__ CUtensorMap tmW2s,
       const __grid_constant__ CUtensorMap tmWos, const __nv_bfloat16* __restrict__ b2,
       __nv_bfloat16* __restrict__ out) {
  extern __shared__ uint8_t smem_raw[];
  const uint32_t sb = (smem_u32(smem_raw) + 1023u) & ~1023u;
  const uint32_t sRed = sb + K3_NST * K3_STAGE, barF = sRed + K3_RED, barE = barF + 8 * K3_NST, barR = barE + 8 * K3_NST;
  const int tid = threadIdx.x, lane = tid & 31;
  const int warp = __shfl_sync(0xffffffffu, tid >> 5, 0);
  const uint32_t rank = cluster_rank();
  const int tile = blockIdx.x >> 1, rb = tile >> 2, ct = tile & 3;
  if (tid == 0) {
    prefetch_tmap(&tmW2); prefetch_tmap(&tmWo); prefetch_tmap(&tmW2s); prefetch_tmap(&tmWos);
    for (int i = 0; i < K3_NST; i++) { mbar_init(barF + 8 * i, 1); mbar_init(barE + 8 * i, 8); }
    mbar_init(barR, 1);
    fence_barrier_init();
    mbar_expect_tx(barR, K3_RED);
  }
  __syncwarp();
  cluster_arrive_relaxed();
  cluster_wait();
  if (warp >= 8) {
    if (lane == 0) {
      const int s0 = rank * 37, pw = warp - 8, bcol = ct * 160 + (ct & 1) * 32, scol = ct * 160 + ((ct & 1) ? 0 : 128);
      const uint8_t* asrc = g_A2 + (size_t)rb * 296 * 2048;
#pragma unroll 1
      for (int i = 0; i < 37; i++) {
        const int st = i & (K3_NST - 1), s = s0 + i;
        if (i >= K3_NST) mbar_wait(barE + 8 * st, ((i / K3_NST) - 1) & 1);
        if (s == 54) pdl_wait();
        const CUtensorMap* m = s < 54 ? &tmW2 : &tmWo;
        const int k = (s < 54 ? s : s - 54) * 32;
        const uint32_t dst = sb + st * K3_STAGE;
        if (pw == 0) {
          mbar_expect_tx(barF + 8 * st, K3_STAGE);
          bulk_g2s(dst + 10240, asrc + (size_t)s * 8192, 8192, barF + 8 * st);
          tma_2d(dst + 8192, s < 54 ? &tmW2s : &tmWos, scol, k, barF + 8 * st);
        } else {
          tma_2d(dst, m, bcol, k, barF + 8 * st);
          tma_2d(dst + 4096, m, bcol + 64, k, barF + 8 * st);
        }
      }
    }
  } else {
    const int wgi = warp >> 2, wq = warp & 3, g = lane >> 2, t4 = lane & 3;
    const int rloc = wgi * 64 + wq * 16 + g, row = rb * 128 + rloc;
    const int col0 = ct * 160 + rank * 80 + t4 * 2;
    uint32_t bias[10];
#pragma unroll
    for (int j = 0; j < 10; j++) bias[j] = __ldg(reinterpret_cast<const uint32_t*>(b2 + col0 + j * 8));
    const float w0 = 1.f - g_gate[row], w1 = 1.f - g_gate[row + 8];
    float big[64], sml[16];
    const uint64_t dA0 = mk_desc(sb + 10240 + wgi * 1024, 2048, 128, 0);
    const uint64_t dBb = mk_desc(sb, 4096, 1024, 1), dBs = mk_desc(sb + 8192, 2048, 512, 2);
    const int nsw = rank ? 17 : 37;
    fence_regs(big); fence_regs(sml);
#pragma unroll 1
    for (int i = 0; i < 37; i++) {
      const int st = i & (K3_NST - 1);
      mbar_wait(barF + 8 * st, (i / K3_NST) & 1);
      const uint32_t off = st * (K3_STAGE >> 4);
      wg_fence();
      wgmma_ssp_n128_t01(big, dA0 + off, dBb + off, i);
      wgmma_ssp_n32_t01(sml, dA0 + off, dBs + off, i);
      wgmma_ssp_n128_t01(big, dA0 + (off + 256), dBb + (off + 128), 1);
      wgmma_ssp_n32_t01(sml, dA0 + (off + 256), dBs + (off + 64), 1);
      wg_commit();
      if (i + 1 == nsw) {
        wg_wait<0>();
        fence_regs(big); fence_regs(sml);
#pragma unroll
        for (int j = 0; j < 16; j++) { big[4 * j] *= w0; big[4 * j + 1] *= w0; big[4 * j + 2] *= w1; big[4 * j + 3] *= w1; }
#pragma unroll
        for (int j = 0; j < 4; j++) { sml[4 * j] *= w0; sml[4 * j + 1] *= w0; sml[4 * j + 2] *= w1; sml[4 * j + 3] *= w1; }
        fence_regs(big); fence_regs(sml);
      } else {
        wg_wait<1>();
      }
      if (i > 0 && lane == 0) mbar_arrive(barE + 8 * ((i - 1) & (K3_NST - 1)));
    }
    wg_wait<0>();
    fence_regs(big); fence_regs(sml);
    const uint32_t peerRed = mapa(sRed, rank ^ 1) + tid * 16, peerBar = mapa(barR, rank ^ 1);
    auto finish = [&](auto odd_c, auto rank_c) {
      constexpr bool ODD = decltype(odd_c)::value, RK = decltype(rank_c)::value;
      auto val = [&](int j, int e) -> float { return ODD ? (j < 4 ? sml[4 * j + e] : big[4 * (j - 4) + e]) : (j < 16 ? big[4 * j + e] : sml[4 * (j - 16) + e]); };
#pragma unroll
      for (int j = 0; j < 10; j++) {
        const int js = RK ? j : 10 + j;
        asm volatile("st.async.weak.shared::cluster.mbarrier::complete_tx::bytes.v4.f32 [%0], {%1, %2, %3, %4}, [%5];"
                     ::"r"(peerRed + j * 4096), "f"(val(js, 0)), "f"(val(js, 1)), "f"(val(js, 2)), "f"(val(js, 3)), "r"(peerBar) : "memory");
      }
      mbar_wait(barR, 0);
      uint32_t r0[10], r1[10];
#pragma unroll
      for (int j = 0; j < 10; j++) {
        const int jk = RK ? 10 + j : j;
        float p0, p1, p2, p3;
        asm volatile("ld.shared.v4.f32 {%0, %1, %2, %3}, [%4];" : "=f"(p0), "=f"(p1), "=f"(p2), "=f"(p3) : "r"(sRed + tid * 16 + j * 4096));
        const float c0 = bf_lo(bias[j]), c1 = bf_hi(bias[j]);
        r0[j] = pack_bf16(fmaf(w0, c0, val(jk, 0) + p0), fmaf(w0, c1, val(jk, 1) + p1));
        r1[j] = pack_bf16(fmaf(w1, c0, val(jk, 2) + p2), fmaf(w1, c1, val(jk, 3) + p3));
      }
      __nv_bfloat16* o0 = out + (size_t)row * D_ + (col0 - t4 * 2);
      const bool odd = t4 & 1, hi = t4 >= 2;
#pragma unroll
      for (int q = 0; q < 2; q++) {
        *reinterpret_cast<uint4*>(o0 + q * 32 + t4 * 8) = quad_transpose(r0[4 * q], r0[4 * q + 1], r0[4 * q + 2], r0[4 * q + 3], odd, hi);
        *reinterpret_cast<uint4*>(o0 + 8 * D_ + q * 32 + t4 * 8) = quad_transpose(r1[4 * q], r1[4 * q + 1], r1[4 * q + 2], r1[4 * q + 3], odd, hi);
      }
      *reinterpret_cast<uint4*>(o0 + (hi ? 8 * D_ : 0) + 64 + (odd ? 8 : 0)) = quad_transpose(r0[8], r0[9], r1[8], r1[9], odd, hi);
    };
    if (ct & 1) { if (rank) finish(std::true_type{}, std::true_type{}); else finish(std::true_type{}, std::false_type{}); }
    else { if (rank) finish(std::false_type{}, std::true_type{}); else finish(std::false_type{}, std::false_type{}); }
  }
}

typedef CUresult (*EncodeFn)(CUtensorMap*, CUtensorMapDataType, cuuint32_t, void*, const cuuint64_t*, const cuuint64_t*, const cuuint32_t*,
                             const cuuint32_t*, CUtensorMapInterleave, CUtensorMapSwizzle, CUtensorMapL2promotion, CUtensorMapFloatOOBfill);

void make_map(EncodeFn fn, CUtensorMap* m, const void* ptr, uint64_t inner, uint64_t outer, uint32_t box_inner, uint32_t box_outer, CUtensorMapSwizzle sw) {
  cuuint64_t dims[2] = {inner, outer};
  cuuint64_t strides[1] = {inner * 2};
  cuuint32_t box[2] = {box_inner, box_outer};
  cuuint32_t es[2] = {1, 1};
  fn(m, CU_TENSOR_MAP_DATA_TYPE_BFLOAT16, 2, const_cast<void*>(ptr), dims, strides, box, es, CU_TENSOR_MAP_INTERLEAVE_NONE, sw,
     CU_TENSOR_MAP_L2_PROMOTION_L2_256B, CU_TENSOR_MAP_FLOAT_OOB_FILL_NONE);
}

}

extern "C" void kernel_launch(void* const* d_in, const int* in_sizes, int n_in, void* d_out, int out_size) {
  (void)in_sizes; (void)n_in; (void)out_size;
  const __nv_bfloat16* x = (const __nv_bfloat16*)d_in[0];
  const __nv_bfloat16* wqkv = (const __nv_bfloat16*)d_in[1];
  const __nv_bfloat16* wo = (const __nv_bfloat16*)d_in[2];
  const __nv_bfloat16* w1 = (const __nv_bfloat16*)d_in[4];
  const __nv_bfloat16* b1 = (const __nv_bfloat16*)d_in[5];
  const __nv_bfloat16* w2 = (const __nv_bfloat16*)d_in[6];
  const __nv_bfloat16* b2 = (const __nv_bfloat16*)d_in[7];
  const __nv_bfloat16* gw = (const __nv_bfloat16*)d_in[8];

  static EncodeFn enc = nullptr;
  if (!enc) {
    void* p = nullptr;
    cudaDriverEntryPointQueryResult qr;
    cudaGetDriverEntryPoint("cuTensorMapEncodeTiled", &p, cudaEnableDefault, &qr);
    enc = (EncodeFn)p;
    cudaFuncSetAttribute(k1_proj, cudaFuncAttributeMaxDynamicSharedMemorySize, K1_SMEM);
    cudaFuncSetAttribute(k2_attn, cudaFuncAttributeMaxDynamicSharedMemorySize, AT_SMEM);
    cudaFuncSetAttribute(k3_out, cudaFuncAttributeMaxDynamicSharedMemorySize, K3_SMEM);
  }
  CUtensorMap tmX, tmWqkv, tmW1, tmW2, tmWo, tmW2s, tmWos;
  make_map(enc, &tmX, x, D_, S_, 64, 128, CU_TENSOR_MAP_SWIZZLE_128B);
  make_map(enc, &tmWqkv, wqkv, 3 * D_, D_, 64, 32, CU_TENSOR_MAP_SWIZZLE_128B);
  make_map(enc, &tmW1, w1, F_, D_, 64, 32, CU_TENSOR_MAP_SWIZZLE_128B);
  make_map(enc, &tmW2, w2, D_, F_, 64, 32, CU_TENSOR_MAP_SWIZZLE_128B);
  make_map(enc, &tmWo, wo, D_, D_, 64, 32, CU_TENSOR_MAP_SWIZZLE_128B);
  make_map(enc, &tmW2s, w2, D_, F_, 32, 32, CU_TENSOR_MAP_SWIZZLE_64B);
  make_map(enc, &tmWos, wo, D_, D_, 32, 32, CU_TENSOR_MAP_SWIZZLE_64B);

  cudaStream_t st = cudaStreamPerThread;
  k1_proj<<<128, 384, K1_SMEM, st>>>(tmX, tmWqkv, tmW1, b1, gw, (const uint8_t*)wqkv, (const uint8_t*)w1,
                                     (const uint8_t*)w2, (const uint8_t*)wo);

  cudaLaunchAttribute at[1];
  at[0].id = cudaLaunchAttributeProgrammaticStreamSerialization;
  at[0].val.programmaticStreamSerializationAllowed = 1;
  {
    cudaLaunchConfig_t cfg = {};
    cfg.gridDim = dim3(128); cfg.blockDim = dim3(512); cfg.dynamicSmemBytes = AT_SMEM; cfg.stream = st;
    cfg.attrs = at; cfg.numAttrs = 1;
    cudaLaunchKernelEx(&cfg, k2_attn, 0);
  }
  {
    cudaLaunchConfig_t cfg = {};
    cfg.gridDim = dim3(128); cfg.blockDim = dim3(320); cfg.dynamicSmemBytes = K3_SMEM; cfg.stream = st;
    cfg.attrs = at; cfg.numAttrs = 1;
    cudaLaunchKernelEx(&cfg, k3_out, tmW2, tmWo, tmW2s, tmWos, b2, (__nv_bfloat16*)d_out);
  }
}
```
